```python
import torch

def _softmax(x, axis=-1):
    return torch.softmax(x, dim=axis)
def _gelu(x):
    return torch.nn.functional.gelu(x, approximate="tanh")
def _silu(x):
    return torch.nn.functional.silu(x)
def _sigmoid(x):
    return torch.sigmoid(x)
def _layernorm(x, axis=-1, eps=1e-5):
    m = x.mean(dim=axis, keepdim=True)
    v = x.var(dim=axis, keepdim=True, unbiased=False)
    return (x - m) / torch.sqrt(v + eps)
def _scatter_add(tgt, idx, src, axis=0):
    return tgt.clone().index_add_(axis, idx, src)
def _segment_sum(src, seg, n):
    out = torch.zeros((n,) + src.shape[1:], dtype=src.dtype)
    return out.index_add_(0, seg, src)
def _pad(x, pw):
    flat = tuple(v for pair in reversed(pw) for v in pair)
    return torch.nn.functional.pad(x, flat)

kernel_name = 'concat_heads__grouped_kv_mqa__mha_block__prompt'

def setup_inputs():

    _w = (lambda a: (lambda t: t.to(torch.bfloat16) if t.is_floating_point() else t)(torch.as_tensor(a)))
    def _A_setup():
        B, S, D, H = 1, 2048, 1024, 32
        Dh = D // H
        return {
            "x": _w((lambda *s: torch.randn(*s, dtype=torch.bfloat16) * 0.05)(B, S, D)),
            "wq": _w((lambda *s: torch.randn(*s, dtype=torch.bfloat16) * 0.8)(D, H * Dh)),
            "wk": _w((lambda *s: torch.randn(*s, dtype=torch.bfloat16) * 0.8)(D, Dh)),
            "wv": _w((lambda *s: torch.randn(*s, dtype=torch.bfloat16) * 0.1)(D, Dh)),
            "wo": _w((lambda *s: torch.randn(*s, dtype=torch.bfloat16) * 0.1)(H * Dh, D)),
        }
    _A_in = _A_setup()

    def _B_setup():
        B, S, D, H = 1, 2048, 1024, 32
        return {
            "x": _w((lambda *s: torch.randn(*s, dtype=torch.bfloat16) * 0.2)(B, S, D)),
            "wqkv": _w((lambda *s: torch.randn(*s, dtype=torch.bfloat16) * 0.2)(D, 3 * D)),
            "wo": _w((lambda *s: torch.randn(*s, dtype=torch.bfloat16) * 0.05)(D, D)),
        }
    _B_in = _B_setup()

    return {
        "A_x": _A_in["x"],
        "A_wq": _A_in["wq"],
        "A_wk": _A_in["wk"],
        "A_wv": _A_in["wv"],
        "A_wo": _A_in["wo"],
        "B_x": _B_in["x"],
        "B_wqkv": _B_in["wqkv"],
        "B_wo": _B_in["wo"],
    }

def reference(A_x, A_wq, A_wk, A_wv, A_wo, B_x, B_wqkv, B_wo):
    def _A_ref(x, wq, wk, wv, wo):
        B, S, D = x.shape
        H = 32
        Dh = D // H
        q = (lambda x, *d: x.permute(*d))((x @ wq).reshape(B, S, H, Dh), 0, 2, 1, 3)
        k = x @ wk
        v = x @ wv
        scores = torch.einsum("bhqd,bkd->bhqk", q, k) * (Dh ** -0.5)
        p = _softmax(scores, axis=-1)
        o = torch.einsum("bhqk,bkd->bhqd", p, v)
        return (lambda x, *d: x.permute(*d))(o, 0, 2, 1, 3).reshape(B, S, H * Dh) @ wo

    def _B_ref(x, wqkv, wo):
        B, S, D = x.shape
        H = 32
        Dh = D // H
        qkv = (lambda x, *d: x.permute(*d))((x @ wqkv).reshape(B, S, 3, H, Dh), 2, 0, 3, 1, 4)
        q, k, v = qkv[0], qkv[1], qkv[2]
        scores = torch.einsum("bhqd,bhkd->bhqk", q, k) * (Dh ** -0.5)
        p = _softmax(scores, axis=-1)
        o = torch.einsum("bhqk,bhkd->bhqd", p, v)
        return (lambda x, *d: x.permute(*d))(o, 0, 2, 1, 3).reshape(B, S, D) @ wo

    a = _A_ref(A_x, A_wq, A_wk, A_wv, A_wo)
    b = _B_ref(B_x, B_wqkv, B_wo)
    return torch.concatenate([a, b], axis=-1)
```

```cpp
#include <cuda_runtime.h>
#include <cuda_bf16.h>
#include <cuda.h>
#include <stdint.h>

namespace {

constexpr int SEQ = 2048;
constexpr int NMAIN = 128, NAUX = 4, NCTA = NMAIN + NAUX;
constexpr int NTHREADS = 640;
constexpr int NG = 3;
constexpr int GSTAGE = 49152;
constexpr int NKV = 5;
constexpr int KVSTAGE = 16384;
constexpr int OFF_KV = NG * GSTAGE;
constexpr int OFF_ONES = OFF_KV + NKV * KVSTAGE;
constexpr int OFF_BAR = OFF_ONES + 1024;
constexpr int BAR_GFULL = OFF_BAR, BAR_GEMPTY = BAR_GFULL + 8 * NG;
constexpr int BAR_KFULL = BAR_GEMPTY + 8 * NG, BAR_KEMPTY = BAR_KFULL + 8 * NKV;
constexpr int OFF_QLIM = BAR_KEMPTY + 8 * NKV;
constexpr int OFF_CONST = OFF_QLIM + 16;
constexpr int SMEM_BYTES = OFF_BAR + 256 + 1024;

constexpr float QSCALE = 0.17677669529663687f * 1.4426950408889634f;
constexpr float S_BOUND2 = 64.f * 64.f * 0.97f;
constexpr float V_LO2 = 8.2718061e-25f;
constexpr float V_HI2 = 1.2089258e24f;

struct Maps { CUtensorMap xA, xB, wq, wqkv, wk, wv, woA, woB, o, out; };

__device__ __align__(1024) __nv_bfloat16 g_K[33 * SEQ * 32];
__device__ __align__(1024) __nv_bfloat16 g_V[33 * SEQ * 32];
__device__ __align__(1024) __nv_bfloat16 g_O[2 * SEQ * 1024];
constexpr int SY_KV = 0, SY_O = 9, SY_DONE = 41, SY_N = 42;
__device__ uint32_t g_sync[SY_N * 32];
__device__ uint32_t g_norm[2 * 33];
#define PROF(i)

__device__ __forceinline__ void wg_fence() { asm volatile("wgmma.fence.sync.aligned;" ::: "memory"); }
__device__ __forceinline__ void wg_commit() { asm volatile("wgmma.commit_group.sync.aligned;" ::: "memory"); }
template <int N> __device__ __forceinline__ void wg_wait() { asm volatile("wgmma.wait_group.sync.aligned %0;" ::"n"(N) : "memory"); }
template <int N> __device__ __forceinline__ void pin(float (&d)[N]) {
#pragma unroll
  for (int i = 0; i < N; i++) asm volatile("" : "+f"(d[i])::"memory");
}
template <int N> __device__ __forceinline__ void pin(uint32_t (&d)[N]) {
#pragma unroll
  for (int i = 0; i < N; i++) asm volatile("" : "+r"(d[i])::"memory");
}
#define F4(a, i) "+f"(a[i]), "+f"(a[i + 1]), "+f"(a[i + 2]), "+f"(a[i + 3])
#define F16(a, i) F4(a, i), F4(a, i + 4), F4(a, i + 8), F4(a, i + 12)
#define R20 "%0,%1,%2,%3,%4,%5,%6,%7,%8,%9,%10,%11,%12,%13,%14,%15,%16,%17,%18,%19"
#define R32 R20 ",%20,%21,%22,%23,%24,%25,%26,%27,%28,%29,%30,%31"
#define R64 R32 ",%32,%33,%34,%35,%36,%37,%38,%39,%40,%41,%42,%43,%44,%45,%46,%47,%48,%49,%50,%51,%52,%53,%54,%55,%56,%57,%58,%59,%60,%61,%62,%63"

__device__ __forceinline__ void mma_ss128(float (&d)[64], uint64_t a, uint64_t b, int acc) {
  asm volatile("{\n.reg .pred p;\nsetp.ne.b32 p, %66, 0;\n"
               "wgmma.mma_async.sync.aligned.m64n128k16.f32.bf16.bf16 {" R64 "}, %64, %65, p, 1, 1, 0, 1;\n}\n"
               : F16(d, 0), F16(d, 16), F16(d, 32), F16(d, 48) : "l"(a), "l"(b), "r"(acc));
}
__device__ __forceinline__ void mma_ss64(float (&d)[32], uint64_t a, uint64_t b, int acc) {
  asm volatile("{\n.reg .pred p;\nsetp.ne.b32 p, %34, 0;\n"
               "wgmma.mma_async.sync.aligned.m64n64k16.f32.bf16.bf16 {" R32 "}, %32, %33, p, 1, 1, 0, 1;\n}\n"
               : F16(d, 0), F16(d, 16) : "l"(a), "l"(b), "r"(acc));
}
template <int ACC>
__device__ __forceinline__ void mma_qk(float (&d)[32], uint32_t a0, uint32_t a1, uint32_t a2, uint32_t a3, uint64_t b) {
  asm volatile("{\n.reg .pred p;\nsetp.ne.b32 p, %37, 0;\n"
               "wgmma.mma_async.sync.aligned.m64n64k16.f32.bf16.bf16 {" R32 "}, {%32,%33,%34,%35}, %36, p, 1, 1, 0;\n}\n"
               : F16(d, 0), F16(d, 16) : "r"(a0), "r"(a1), "r"(a2), "r"(a3), "l"(b), "n"(ACC));
}
__device__ __forceinline__ void mma_pv(float (&d)[20], uint32_t a0, uint32_t a1, uint32_t a2, uint32_t a3, uint64_t b) {
  asm volatile("{\n.reg .pred p;\nsetp.ne.b32 p, 1, 0;\n"
               "wgmma.mma_async.sync.aligned.m64n40k16.f32.bf16.bf16 {" R20 "}, {%20,%21,%22,%23}, %24, p, 1, 1, 1;\n}\n"
               : F16(d, 0), F4(d, 16) : "r"(a0), "r"(a1), "r"(a2), "r"(a3), "l"(b));
}

__device__ __forceinline__ void mbar_init(uint32_t mb, uint32_t n) { asm volatile("mbarrier.init.shared::cta.b64 [%0], %1;" ::"r"(mb), "r"(n) : "memory"); }
__device__ __forceinline__ void mbar_wait(uint32_t mb, uint32_t par) {
  asm volatile("{\n.reg .pred p;\n.reg .u32 n;\n"
               "mbarrier.try_wait.parity.shared::cta.b64 p, [%0], %1;\n@p bra.uni DONE;\nmov.u32 n, 0;\n"
               "LOOP:\nmbarrier.try_wait.parity.shared::cta.b64 p, [%0], %1;\nadd.u32 n, n, 1;\n"
               "setp.gt.or.u32 p, n, 131072, p;\n@!p bra.uni LOOP;\nDONE:\n}" ::"r"(mb), "r"(par) : "memory");
}
__device__ __forceinline__ void mbar_arrive(uint32_t mb) { asm volatile("mbarrier.arrive.shared::cta.b64 _, [%0];" ::"r"(mb) : "memory"); }
__device__ __forceinline__ void mbar_expect(uint32_t mb, uint32_t bytes) { asm volatile("mbarrier.arrive.expect_tx.shared::cta.b64 _, [%0], %1;" ::"r"(mb), "r"(bytes) : "memory"); }
__device__ __forceinline__ void tma_load(uint32_t dst, const CUtensorMap* m, int c0, int c1, uint32_t mb) {
  asm volatile("cp.async.bulk.tensor.2d.shared::cluster.global.mbarrier::complete_tx::bytes [%0], [%1, {%3, %4}], [%2];"
               ::"r"(dst), "l"(m), "r"(mb), "r"(c0), "r"(c1) : "memory");
}
__device__ __forceinline__ void tma_store(const CUtensorMap* m, uint32_t src, int c0, int c1) {
  asm volatile("cp.async.bulk.tensor.2d.global.shared::cta.bulk_group [%0, {%2, %3}], [%1];" ::"l"(m), "r"(src), "r"(c0), "r"(c1) : "memory");
}
__device__ __forceinline__ void bulk_load(uint32_t dst, const void* src, uint32_t bytes, uint32_t mb) {
  asm volatile("cp.async.bulk.shared::cluster.global.mbarrier::complete_tx::bytes [%0], [%1], %2, [%3];"
               ::"r"(dst), "l"(src), "r"(bytes), "r"(mb) : "memory");
}
__device__ __forceinline__ void fence_async() { asm volatile("fence.proxy.async;" ::: "memory"); }
__device__ __forceinline__ void signal(int idx) {
  asm volatile("fence.acq_rel.gpu;\nred.relaxed.gpu.global.add.u32 [%0], 1;" ::"l"(g_sync + idx * 32) : "memory");
}
__device__ __forceinline__ void poll(int idx, uint32_t target) {
  uint32_t v, n = 0;
  while (true) {
    asm volatile("ld.acquire.gpu.global.u32 %0, [%1];" : "=r"(v) : "l"(g_sync + idx * 32) : "memory");
    if (v >= target || ++n > (1u << 20)) break;
    __nanosleep(40);
  }
  fence_async();
}
__device__ __forceinline__ float ex2(float x) { float y; asm("ex2.approx.ftz.f32 %0, %1;" : "=f"(y) : "f"(x)); return y; }
__device__ __forceinline__ uint32_t pack(float lo, float hi) { uint32_t r; asm("cvt.rn.bf16x2.f32 %0, %1, %2;" : "=r"(r) : "f"(hi), "f"(lo)); return r; }
__device__ __forceinline__ void stsm4(uint32_t addr, uint32_t a, uint32_t b, uint32_t c, uint32_t d) {
  asm volatile("stmatrix.sync.aligned.m8n8.x4.shared.b16 [%0], {%1,%2,%3,%4};" ::"r"(addr), "r"(a), "r"(b), "r"(c), "r"(d) : "memory");
}
__device__ __forceinline__ void lds128(uint32_t addr, uint32_t& a, uint32_t& b, uint32_t& c, uint32_t& d) {
  asm volatile("ld.shared.v4.b32 {%0,%1,%2,%3}, [%4];" : "=r"(a), "=r"(b), "=r"(c), "=r"(d) : "r"(addr) : "memory");
}

__device__ __forceinline__ uint32_t exp2_pair(float s0, float s1, uint32_t beta) {
  const uint32_t z0 = __float_as_uint(s0 + 32895.f), z1 = __float_as_uint(s1 + 32895.f);
  const uint32_t u = __byte_perm(z0, z1, 0x6420), e = __byte_perm(z0, z1, 0x5612);
  uint32_t y, t, d;
  asm("fma.rn.f16x2 %0, %1, %2, %3;" : "=r"(y) : "r"(u), "r"(beta), "r"(0x34833483u));
  asm("fma.rn.f16x2 %0, %1, %1, %2;" : "=r"(t) : "r"(y), "r"(0x344c344cu));
  asm("mul.rn.f16x2 %0, %1, %2;" : "=r"(d) : "r"(t), "r"(u));
  return (e >> 1) + d;
}

struct Ring {
  uint32_t slot, phase;
  template <int N> __device__ __forceinline__ void next() { if (++slot == N) { slot = 0; phase ^= 1; } }
};

__device__ __forceinline__ void gemm128(float (&acc)[64], uint32_t sb, uint32_t wg, bool lane0, Ring& r, int keep) {
  const uint64_t a0 = (uint64_t)((sb + wg * 8192) >> 4) | (1ull << 16) | (64ull << 32) | (1ull << 62);
  const uint64_t b0 = (uint64_t)((sb + 32768) >> 4) | (512ull << 16) | (64ull << 32) | (1ull << 62);
#pragma unroll 1
  for (int kc = 0; kc < 16; kc++) {
    mbar_wait(sb + BAR_GFULL + r.slot * 8, r.phase);
    const uint64_t off = r.slot * (GSTAGE >> 4);
    wg_fence();
#pragma unroll
    for (int k = 0; k < 4; k++) mma_ss128(acc, a0 + off + k * 2, b0 + off + k * 128, kc | k);
    wg_commit();
    wg_wait<0>();
    if (lane0 && kc < 16 - keep) mbar_arrive(sb + BAR_GEMPTY + r.slot * 8);
    r.next<NG>();
  }
  pin(acc);
}

__device__ __forceinline__ uint32_t quad_head_max(float (&v)[8], uint32_t q) {
  float a[4], b[2];
#pragma unroll
  for (int i = 0; i < 4; i++) {
    const float keep = (q & 1) ? v[4 + i] : v[i], send = (q & 1) ? v[i] : v[4 + i];
    a[i] = keep + __shfl_xor_sync(~0u, send, 1);
  }
#pragma unroll
  for (int i = 0; i < 2; i++) {
    const float keep = (q & 2) ? a[2 + i] : a[i], send = (q & 2) ? a[i] : a[2 + i];
    b[i] = keep + __shfl_xor_sync(~0u, send, 2);
  }
  return max(__float_as_uint(b[0]) & 0x7fffffffu, __float_as_uint(b[1]) & 0x7fffffffu);
}

template <bool SAFE>
__device__ __forceinline__ void attn_step(float (&s)[32], float (&o)[20], uint32_t (&q)[8], float (&m)[2], uint64_t vd, uint64_t kd, uint32_t beta) {
  constexpr uint64_t VSTEP = 64ull - (64ull << 16);
  uint32_t p[16];
  if (SAFE) {
    float mx0 = m[0], mx1 = m[1];
#pragma unroll
    for (int i = 0; i < 8; i++) { mx0 = fmaxf(mx0, fmaxf(s[4 * i], s[4 * i + 1])); mx1 = fmaxf(mx1, fmaxf(s[4 * i + 2], s[4 * i + 3])); }
    mx0 = fmaxf(mx0, __shfl_xor_sync(~0u, mx0, 1)); mx1 = fmaxf(mx1, __shfl_xor_sync(~0u, mx1, 1));
    mx0 = fmaxf(mx0, __shfl_xor_sync(~0u, mx0, 2)); mx1 = fmaxf(mx1, __shfl_xor_sync(~0u, mx1, 2));
    const float u0 = mx0 == -INFINITY ? 0.f : mx0, u1 = mx1 == -INFINITY ? 0.f : mx1;
    const float c0 = ex2(m[0] - u0), c1 = ex2(m[1] - u1);
    m[0] = mx0; m[1] = mx1;
#pragma unroll
    for (int i = 0; i < 5; i++) { o[4 * i] *= c0; o[4 * i + 1] *= c0; o[4 * i + 2] *= c1; o[4 * i + 3] *= c1; }
#pragma unroll
    for (int i = 0; i < 8; i++) {
      p[2 * i] = pack(ex2(s[4 * i] - u0), ex2(s[4 * i + 1] - u0));
      p[2 * i + 1] = pack(ex2(s[4 * i + 2] - u1), ex2(s[4 * i + 3] - u1));
    }
    pin(p); pin(o);
    wg_fence();
#pragma unroll
    for (int k = 0; k < 4; k++) mma_pv(o, p[4 * k], p[4 * k + 1], p[4 * k + 2], p[4 * k + 3], vd + k * VSTEP);
  } else {
#pragma unroll
    for (int h = 0; h < 2; h++) {
#pragma unroll
      for (int i = 8 * h; i < 8 * h + 8; i++) {
        if ((i ^ (i >> 1)) & 1) p[i] = pack(ex2(s[2 * i]), ex2(s[2 * i + 1]));
        else p[i] = exp2_pair(s[2 * i], s[2 * i + 1], beta);
        asm volatile("" : "+r"(p[i])::"memory");
      }
      wg_fence();
      mma_pv(o, p[8 * h], p[8 * h + 1], p[8 * h + 2], p[8 * h + 3], vd + (2 * h) * VSTEP);
      mma_pv(o, p[8 * h + 4], p[8 * h + 5], p[8 * h + 6], p[8 * h + 7], vd + (2 * h + 1) * VSTEP);
      if (h == 0) wg_commit();
    }
  }
  mma_qk<0>(s, q[0], q[1], q[2], q[3], kd);
  mma_qk<1>(s, q[4], q[5], q[6], q[7], kd + 2);
  wg_commit();
  wg_wait<0>();
  pin(s); pin(o);
}

__device__ __forceinline__ void load_q(uint32_t (&q)[8], uint32_t addr) {
  lds128(addr, q[0], q[2], q[4], q[6]);
  lds128(addr + 1024, q[1], q[3], q[5], q[7]);
}

template <bool SAFE>
__device__ __forceinline__ void attn_head(float (&s)[32], float (&o)[20], uint32_t (&q)[8], uint32_t sb, Ring& r, bool lane0,
                                          uint32_t qnext, uint32_t beta) {
  constexpr uint64_t VSLOT = (uint64_t)(KVSTAGE >> 4) - ((uint64_t)(KVSTAGE >> 4) << 16);
  const uint64_t vd0 = (uint64_t)((sb + OFF_KV) >> 4) | ((uint64_t)((OFF_ONES - OFF_KV) >> 4) << 16) | (32ull << 32) | (2ull << 62);
  const uint64_t kd0 = (uint64_t)((sb + OFF_KV + 8192) >> 4) | (1ull << 16) | (32ull << 32) | (2ull << 62);
  float m[2] = {-INFINITY, -INFINITY};
#pragma unroll 1
  for (int i = 0; i < 16; i++) {
    mbar_wait(sb + BAR_KFULL + r.slot * 8, r.phase);
    const uint64_t vd = vd0 + r.slot * VSLOT, kd = kd0 + r.slot * (KVSTAGE >> 4);
    attn_step<SAFE>(s, o, q, m, vd, kd, beta);
    if (i == 15 && qnext) load_q(q, qnext);
    pin(q);
    attn_step<SAFE>(s, o, q, m, vd + 256ull - (256ull << 16), kd + 256, beta);
    if (lane0) mbar_arrive(sb + BAR_KEMPTY + r.slot * 8);
    r.next<NKV>();
  }
}

template <int NH, int NACC>
__device__ __forceinline__ void store_kv(float (&acc)[NACC], __nv_bfloat16* dst0, __nv_bfloat16* dst1, size_t hstride, int key, uint32_t q, float (&nrm)[8]) {
#pragma unroll
  for (int h = 0; h < NH; h++) {
    __nv_bfloat16* base = (NH == 2 && h == 1) ? dst1 : dst0 + h * hstride;
#pragma unroll
    for (int r = 0; r < 2; r++) {
      uint32_t w[4];
      float n = 0.f;
#pragma unroll
      for (int j = 0; j < 4; j++) {
        const float x = acc[(h * 4 + j) * 4 + 2 * r], y = acc[(h * 4 + j) * 4 + 2 * r + 1];
        w[j] = pack(x, y);
        n = fmaf(x, x, fmaf(y, y, n));
      }
      nrm[2 * h + r] = n;
      const int kk = key + 8 * r;
      *reinterpret_cast<uint4*>(base + kk * 32 + ((q ^ (kk >> 1)) & 3) * 8) = make_uint4(w[0], w[1], w[2], w[3]);
    }
  }
#pragma unroll
  for (int i = 2 * NH; i < 8; i++) nrm[i] = 0.f;
}

__global__ void __launch_bounds__(NTHREADS, 1) fused_kernel(const __grid_constant__ Maps maps) {
  extern __shared__ __align__(1024) uint8_t smem_raw[];
  const uint32_t sb = ((uint32_t)__cvta_generic_to_shared(smem_raw) + 1023) & ~1023u;
  const uint32_t tid = threadIdx.x, lane = tid & 31;
  const uint32_t wg = __shfl_sync(~0u, tid >> 7, 0);
  const int cta = blockIdx.x;
  const bool aux = cta >= NMAIN;
  const int br = (cta >> 6) & 1, rb = (cta >> 3) & 7, hg = cta & 7;
  const int rb1 = cta >> 4, ct1 = cta & 15;
  PROF(0);

  if (tid == 512) {
    for (int i = 0; i < NG; i++) { mbar_init(sb + BAR_GFULL + i * 8, 1); mbar_init(sb + BAR_GEMPTY + i * 8, 16); }
    for (int i = 0; i < NKV; i++) { mbar_init(sb + BAR_KFULL + i * 8, 1); mbar_init(sb + BAR_KEMPTY + i * 8, 16); }
    asm volatile("st.shared.u32 [%0], %1;" ::"r"(sb + OFF_CONST), "r"(0x725e725eu) : "memory");
    asm volatile("fence.mbarrier_init.release.cluster;" ::: "memory");
  }
  if (tid < 256) asm volatile("st.shared.u32 [%0], %1;" ::"r"(sb + OFF_ONES + tid * 4), "r"(0x3f803f80u) : "memory");
  fence_async();
  __syncthreads();

  if (wg == 4) {
    asm volatile("setmaxnreg.dec.sync.aligned.u32 32;");
    if (tid == 512) {
      Ring g{0, 1};
      if (aux) {
        for (int i = 0; i < 32; i++) {
          const uint32_t st = sb + g.slot * GSTAGE, fb = sb + BAR_GFULL + g.slot * 8;
          mbar_wait(sb + BAR_GEMPTY + g.slot * 8, g.phase);
          mbar_expect(fb, 32768 + 8192);
          tma_load(st, &maps.xA, (i & 15) * 64, (cta - NMAIN) * 512 + (i >> 4) * 256, fb);
          tma_load(st + 32768, &maps.wk, 0, (i & 15) * 64, fb);
          tma_load(st + 32768 + 4096, &maps.wv, 0, (i & 15) * 64, fb);
          g.next<NG>();
        }
      } else {
        for (int i = 0; i < 32; i++) {
          const uint32_t st = sb + g.slot * GSTAGE, fb = sb + BAR_GFULL + g.slot * 8;
          const bool p1 = i < 16;
          const CUtensorMap* mx = (p1 || br) ? &maps.xB : &maps.xA;
          const CUtensorMap* mw = (p1 || br) ? &maps.wqkv : &maps.wq;
          const int row = (p1 ? rb1 : rb) * 256, col = p1 ? 1024 + ct1 * 128 : hg * 128, k = (i & 15) * 64;
          mbar_wait(sb + BAR_GEMPTY + g.slot * 8, g.phase);
          mbar_expect(fb, GSTAGE);
          tma_load(st, mx, k, row, fb);
          tma_load(st + 32768, mw, col, k, fb);
          tma_load(st + 32768 + 8192, mw, col + 64, k, fb);
          if (i == 16 + NG) signal(SY_KV + (ct1 & 7));
          g.next<NG>();
        }
        poll(SY_KV + (br ? hg : 8), br ? 16 : NAUX);
        const int kvh0 = br ? hg * 4 : 32, hstep = br ? 1 : 0;
        for (int h = 0; h < 4; h++) {
          const float kn = __uint_as_float(__ldcg(g_norm + kvh0 + h * hstep)), vn = __uint_as_float(__ldcg(g_norm + 33 + kvh0 + h * hstep));
          const float lim = (vn >= V_LO2 && vn <= V_HI2 && kn <= 1e30f) ? S_BOUND2 / fmaxf(kn, 1e-30f) : -1.f;
          asm volatile("st.shared.f32 [%0], %1;" ::"r"(sb + OFF_QLIM + h * 4), "f"(lim) : "memory");
        }
        Ring r{0, 1};
        for (int t = 0; t < 65; t++) {
          const uint32_t st = sb + OFF_KV + r.slot * KVSTAGE, fb = sb + BAR_KFULL + r.slot * 8;
          mbar_wait(sb + BAR_KEMPTY + r.slot * 8, r.phase);
          const int hn = kvh0 + min(t >> 4, 3) * hstep;
          if (t == 0) {
            mbar_expect(fb, 4096);
          } else {
            const int hc = kvh0 + ((t - 1) >> 4) * hstep, key = ((t - 1) & 15) * 128;
            mbar_expect(fb, KVSTAGE);
            bulk_load(st, g_V + (hc * SEQ + key) * 32, 8192, fb);
            bulk_load(st + 8192, g_K + (hc * SEQ + key + 64) * 32, 4096, fb);
          }
          bulk_load(st + 12288, g_K + (hn * SEQ + (t & 15) * 128) * 32, 4096, fb);
          if (t == 33 + NKV) signal(SY_O + (br * 8 + rb) * 2);
          r.next<NKV>();
        }
        const CUtensorMap* mw = br ? &maps.woB : &maps.woA;
        for (int i = 0; i < 16; i++) {
          const uint32_t st = sb + g.slot * GSTAGE, fb = sb + BAR_GFULL + g.slot * 8;
          const int k = ((i & 7) * 2 + (i >> 3)) * 64;
          if ((i & 7) == 0) poll(SY_O + (br * 8 + rb) * 2 + (i >> 3), 8);
          mbar_wait(sb + BAR_GEMPTY + g.slot * 8, g.phase);
          mbar_expect(fb, GSTAGE);
          tma_load(st, &maps.o, k, br * SEQ + rb * 256, fb);
          tma_load(st + 32768, mw, hg * 128, k, fb);
          tma_load(st + 32768 + 8192, mw, hg * 128 + 64, k, fb);
          if (i == NG) signal(SY_O + (br * 8 + rb) * 2 + 1);
          g.next<NG>();
        }
        __threadfence();
        if (atomicAdd(g_sync + SY_DONE * 32, 1) == NMAIN - 1) {
          for (int i = 0; i < SY_N; i++) g_sync[i * 32] = 0;
          for (int i = 0; i < 66; i++) g_norm[i] = 0;
        }
      }
    }
  } else {
    asm volatile("setmaxnreg.inc.sync.aligned.u32 112;");
    const uint32_t warp = (tid >> 5) & 3, gq = lane >> 2, q4 = lane & 3;
    const bool lane0 = lane == 0;
    const uint32_t hsel = (q4 & 1) * 2 + (q4 >> 1);
    Ring g{0, 0};
    if (aux) {
      const uint64_t a0 = (uint64_t)((sb + wg * 8192) >> 4) | (1ull << 16) | (64ull << 32) | (1ull << 62);
      const uint64_t b0 = (uint64_t)((sb + 32768) >> 4) | (256ull << 16) | (32ull << 32) | (2ull << 62);
#pragma unroll 1
      for (int pass = 0; pass < 2; pass++) {
        float acc[32];
#pragma unroll
        for (int i = 0; i < 32; i++) acc[i] = 0.f;
        pin(acc);
#pragma unroll 1
        for (int kc = 0; kc < 16; kc++) {
          mbar_wait(sb + BAR_GFULL + g.slot * 8, g.phase);
          const uint64_t off = g.slot * (GSTAGE >> 4);
          wg_fence();
#pragma unroll
          for (int k = 0; k < 4; k++) mma_ss64(acc, a0 + off + k * 2, b0 + off + k * 64, 1);
          wg_commit();
          wg_wait<0>();
          if (lane0) mbar_arrive(sb + BAR_GEMPTY + g.slot * 8);
          g.next<NG>();
        }
        pin(acc);
        float nrm[8];
        store_kv<2>(acc, g_K + 32 * SEQ * 32, g_V + 32 * SEQ * 32, 0, (cta - NMAIN) * 512 + pass * 256 + wg * 64 + warp * 16 + gq, q4, nrm);
        uint32_t mx = quad_head_max(nrm, q4);
        mx = max(mx, __shfl_xor_sync(~0u, mx, 4)); mx = max(mx, __shfl_xor_sync(~0u, mx, 8)); mx = max(mx, __shfl_xor_sync(~0u, mx, 16));
        if (lane < 4 && hsel < 2) atomicMax(g_norm + hsel * 33 + 32, mx);
      }
      asm volatile("bar.sync 1, 512;" ::: "memory");
      if (tid == 0) signal(SY_KV + 8);
    } else {
      uint32_t qbad;
      const uint32_t stash = sb + wg * 8192 + warp * 2048;
      const uint32_t srow = (lane & 7) + ((lane >> 3) & 1) * 8;
      {
        float acc[64];
#pragma unroll
        for (int i = 0; i < 64; i++) acc[i] = 0.f;
        pin(acc);
        gemm128(acc, sb, wg, lane0, g, 0);
        PROF(1);
        float nrm[8];
        store_kv<4>(acc, (ct1 < 8 ? g_K : g_V) + (ct1 & 7) * 4 * SEQ * 32, nullptr, SEQ * 32, rb1 * 256 + wg * 64 + warp * 16 + gq, q4, nrm);
        uint32_t mx = quad_head_max(nrm, q4);
        mx = max(mx, __shfl_xor_sync(~0u, mx, 4)); mx = max(mx, __shfl_xor_sync(~0u, mx, 8)); mx = max(mx, __shfl_xor_sync(~0u, mx, 16));
        if (lane < 4) atomicMax(g_norm + (ct1 >> 3) * 33 + (ct1 & 7) * 4 + hsel, mx);
        __syncwarp();
        PROF(2);
        gemm128(acc, sb, wg, lane0, g, 2);
        PROF(3);
#pragma unroll
        for (int i = 0; i < 8; i++) nrm[i] = 0.f;
#pragma unroll
        for (int j = 0; j < 16; j += 2) {
          uint32_t w[4];
#pragma unroll
          for (int i = 0; i < 4; i++) {
            const float x = acc[4 * j + 2 * i] * QSCALE, y = acc[4 * j + 2 * i + 1] * QSCALE;
            w[i] = pack(x, y);
            nrm[(j >> 2) * 2 + (i & 1)] = fmaf(x, x, fmaf(y, y, nrm[(j >> 2) * 2 + (i & 1)]));
          }
          stsm4(stash + (j >> 3) * GSTAGE + srow * 128 + ((((j & 7) + (lane >> 4)) ^ (lane & 7)) << 4), w[0], w[1], w[2], w[3]);
        }
        const float qn = __uint_as_float(quad_head_max(nrm, q4));
        __syncwarp();
        mbar_wait(sb + BAR_KFULL, 0);
        float lim;
        asm volatile("ld.shared.f32 %0, [%1];" : "=f"(lim) : "r"(sb + OFF_QLIM + hsel * 4) : "memory");
        const uint32_t bad = !(qn <= lim);
        qbad = 0;
#pragma unroll
        for (int h = 0; h < 4; h++) {
          uint32_t any;
          asm volatile("{\n.reg .pred p, r;\nsetp.ne.u32 p, %2, 0;\nbarrier.red.or.pred r, %1, 128, p;\nselp.u32 %0, 1, 0, r;\n}"
                       : "=r"(any) : "r"(wg + 1), "r"(bad && hsel == h ? 1u : 0u) : "memory");
          qbad |= any << h;
        }
      }
      {
        float s[32], o[20];
        uint32_t q[8], beta;
        asm volatile("ld.shared.u32 %0, [%1];" : "=r"(beta) : "r"(sb + OFF_CONST) : "memory");
        const uint32_t qaddr = stash + gq * 128;
        load_q(q, qaddr + ((q4 ^ gq) << 4));
#pragma unroll
        for (int i = 0; i < 32; i++) s[i] = 0.f;
        pin(s); pin(q);
        wg_fence();
        {
          const uint64_t kd = (uint64_t)((sb + OFF_KV + 12288) >> 4) | (1ull << 16) | (32ull << 32) | (2ull << 62);
          mma_qk<0>(s, q[0], q[1], q[2], q[3], kd);
          mma_qk<1>(s, q[4], q[5], q[6], q[7], kd + 2);
        }
        wg_commit();
        wg_wait<0>();
        pin(s);
        if (lane0) mbar_arrive(sb + BAR_KEMPTY);
        Ring r{1, 0};
        PROF(4);
        __nv_bfloat16* orow = g_O + (size_t)(br * SEQ + rb * 256 + wg * 64 + warp * 16 + gq) * 1024 + hg * 128 + q4 * 8;
#pragma unroll 1
        for (int h = 0; h < 4; h++) {
#pragma unroll
          for (int i = 0; i < 20; i++) o[i] = 0.f;
          pin(o);
          const uint32_t hn = h + 1;
          const uint32_t qnext = h == 3 ? 0 : qaddr + (hn >> 1) * GSTAGE + (((((hn & 1) << 2) + q4) ^ gq) << 4);
          if (__any_sync(~0u, (qbad >> h) & 1)) attn_head<true>(s, o, q, sb, r, lane0, qnext, beta);
          else attn_head<false>(s, o, q, sb, r, lane0, qnext, beta);
          const float i0 = 1.f / o[16], i1 = 1.f / o[18];
          *reinterpret_cast<uint4*>(orow + h * 32) =
              make_uint4(pack(o[0] * i0, o[1] * i0), pack(o[4] * i0, o[5] * i0), pack(o[8] * i0, o[9] * i0), pack(o[12] * i0, o[13] * i0));
          *reinterpret_cast<uint4*>(orow + h * 32 + 8 * 1024) =
              make_uint4(pack(o[2] * i1, o[3] * i1), pack(o[6] * i1, o[7] * i1), pack(o[10] * i1, o[11] * i1), pack(o[14] * i1, o[15] * i1));
          if (h == 2) {
            fence_async();
            __syncwarp();
            if (lane0) { mbar_arrive(sb + BAR_GEMPTY); mbar_arrive(sb + BAR_GEMPTY + 8); }
          }
          __syncwarp();
          PROF(5 + h);
        }
      }
      {
        float acc[64];
#pragma unroll
        for (int i = 0; i < 64; i++) acc[i] = 0.f;
        pin(acc);
        gemm128(acc, sb, wg, lane0, g, 0);
        PROF(9);
        const uint32_t stage = sb + OFF_KV + (wg * 4 + warp) * 4096;
#pragma unroll
        for (int j = 0; j < 16; j += 2) {
          stsm4(stage + (j >> 3) * 2048 + srow * 128 + ((((j & 7) + (lane >> 4)) ^ (lane & 7)) << 4),
                pack(acc[4 * j], acc[4 * j + 1]), pack(acc[4 * j + 2], acc[4 * j + 3]),
                pack(acc[4 * j + 4], acc[4 * j + 5]), pack(acc[4 * j + 6], acc[4 * j + 7]));
        }
        fence_async();
        __syncwarp();
        if (lane0) {
          const int row = rb * 256 + wg * 64 + warp * 16, col = br * 1024 + hg * 128;
          tma_store(&maps.out, stage, col, row);
          tma_store(&maps.out, stage + 2048, col + 64, row);
          asm volatile("cp.async.bulk.commit_group;\ncp.async.bulk.wait_group 0;" ::: "memory");
        }
        PROF(10);
      }
    }
  }
}

typedef CUresult (*EncodeFn)(CUtensorMap*, CUtensorMapDataType, cuuint32_t, void*, const cuuint64_t*, const cuuint64_t*,
                             const cuuint32_t*, const cuuint32_t*, CUtensorMapInterleave, CUtensorMapSwizzle,
                             CUtensorMapL2promotion, CUtensorMapFloatOOBfill);

void make_map(EncodeFn enc, CUtensorMap* m, void* p, uint64_t cols, uint64_t rows, uint32_t bc, uint32_t brows, CUtensorMapSwizzle sw) {
  cuuint64_t dims[2] = {cols, rows}, strides[1] = {cols * 2};
  cuuint32_t box[2] = {bc, brows}, es[2] = {1, 1};
  enc(m, CU_TENSOR_MAP_DATA_TYPE_BFLOAT16, 2, p, dims, strides, box, es, CU_TENSOR_MAP_INTERLEAVE_NONE, sw,
      CU_TENSOR_MAP_L2_PROMOTION_L2_128B, CU_TENSOR_MAP_FLOAT_OOB_FILL_NONE);
}

}

extern "C" void kernel_launch(void* const* d_in, const int* in_sizes, int n_in, void* d_out, int out_size) {
  static EncodeFn enc = nullptr;
  static void* o_ptr = nullptr;
  if (!enc) {
    void* fn = nullptr;
    cudaDriverEntryPointQueryResult qr;
    cudaGetDriverEntryPoint("cuTensorMapEncodeTiled", &fn, cudaEnableDefault, &qr);
    enc = (EncodeFn)fn;
    cudaGetSymbolAddress(&o_ptr, g_O);
    cudaFuncSetAttribute(fused_kernel, cudaFuncAttributeMaxDynamicSharedMemorySize, SMEM_BYTES);
  }
  Maps m;
  const CUtensorMapSwizzle S128 = CU_TENSOR_MAP_SWIZZLE_128B, S64 = CU_TENSOR_MAP_SWIZZLE_64B;
  make_map(enc, &m.xA, d_in[0], 1024, SEQ, 64, 256, S128);
  make_map(enc, &m.wq, d_in[1], 1024, 1024, 64, 64, S128);
  make_map(enc, &m.wk, d_in[2], 32, 1024, 32, 64, S64);
  make_map(enc, &m.wv, d_in[3], 32, 1024, 32, 64, S64);
  make_map(enc, &m.woA, d_in[4], 1024, 1024, 64, 64, S128);
  make_map(enc, &m.xB, d_in[5], 1024, SEQ, 64, 256, S128);
  make_map(enc, &m.wqkv, d_in[6], 3072, 1024, 64, 64, S128);
  make_map(enc, &m.woB, d_in[7], 1024, 1024, 64, 64, S128);
  make_map(enc, &m.o, o_ptr, 1024, 2 * SEQ, 64, 256, S128);
  make_map(enc, &m.out, d_out, 2048, SEQ, 64, 16, S128);
  fused_kernel<<<NCTA, NTHREADS, SMEM_BYTES>>>(m);
}
```

```cpp
#include <cuda_runtime.h>
#include <cuda_bf16.h>
#include <cuda.h>
#include <stdint.h>

namespace {

constexpr int SEQ = 2048;
constexpr int NMAIN = 128, NAUX = 4, NCTA = NMAIN + NAUX;
constexpr int NTHREADS = 640;
constexpr int NG = 3;
constexpr int GSTAGE = 49152;
#define KSTEPS 4
constexpr int NKV = 8 / KSTEPS;
constexpr int KVSTAGE = KSTEPS * 8192;
constexpr int OFF_KV = NG * GSTAGE;
constexpr int OFF_K0 = OFF_KV + NKV * KVSTAGE;
constexpr int OFF_ONES = OFF_K0 + 4096;
constexpr int OFF_BAR = OFF_ONES + 1024;
constexpr int BAR_GFULL = OFF_BAR, BAR_GEMPTY = BAR_GFULL + 8 * NG;
constexpr int BAR_KFULL = BAR_GEMPTY + 8 * NG, BAR_KEMPTY = BAR_KFULL + 8 * NKV;
constexpr int BAR_K0 = BAR_KEMPTY + 8 * NKV;
constexpr int BAR_ST = BAR_K0 + 8;
constexpr int BAR_OD = BAR_ST + 32;
constexpr int OFF_QLIM = BAR_OD + 8;
constexpr int OFF_CONST = OFF_QLIM + 16;
constexpr int OFF_NRM = OFF_BAR + 240;
constexpr int SMEM_BYTES = OFF_BAR + 256 + 1024 + 2560;

constexpr float QSCALE = 0.17677669529663687f * 1.4426950408889634f;
constexpr float S_BOUND2 = 64.f * 64.f * 0.97f;
constexpr float CV = 0.70703125f;
constexpr float CV_LOG2 = 0.50015411f;
constexpr float H_LO2 = 9.5367432e-7f, H_HI2 = 1048576.f;
constexpr float V_LO2 = 8.2718061e-25f;
constexpr float V_HI2 = 1.2089258e24f;

struct Maps { CUtensorMap xA, xB, wq, wqkv, wk, wv, woA, woB, o, out; uint64_t kvdesc; };

__device__ __align__(1024) __nv_bfloat16 g_K[33 * SEQ * 32];
__device__ __align__(1024) __nv_bfloat16 g_V[33 * SEQ * 32];
__device__ __align__(1024) __nv_bfloat16 g_O[2 * SEQ * 1024];
constexpr int SY_KV = 0, SY_O = 9, SY_DONE = 41, SY_N = 42;
__device__ uint32_t g_sync[SY_N * 32];
__device__ __align__(16) float g_kscale[33 * 128];
__device__ uint4 g_norm[NCTA];
#define PROF(i)
#define PROFX(i)
#define PROF_GT(j)
#define PROF_DUMP()

__device__ __forceinline__ void wg_fence() { asm volatile("wgmma.fence.sync.aligned;" ::: "memory"); }
__device__ __forceinline__ void wg_commit() { asm volatile("wgmma.commit_group.sync.aligned;" ::: "memory"); }
template <int N> __device__ __forceinline__ void wg_wait() { asm volatile("wgmma.wait_group.sync.aligned %0;" ::"n"(N) : "memory"); }
template <int N> __device__ __forceinline__ void pin(float (&d)[N]) {
#pragma unroll
  for (int i = 0; i < N; i++) asm volatile("" : "+f"(d[i])::"memory");
}
template <int N> __device__ __forceinline__ void pin(uint32_t (&d)[N]) {
#pragma unroll
  for (int i = 0; i < N; i++) asm volatile("" : "+r"(d[i])::"memory");
}
#define F4(a, i) "+f"(a[i]), "+f"(a[i + 1]), "+f"(a[i + 2]), "+f"(a[i + 3])
#define F16(a, i) F4(a, i), F4(a, i + 4), F4(a, i + 8), F4(a, i + 12)
#define R20 "%0,%1,%2,%3,%4,%5,%6,%7,%8,%9,%10,%11,%12,%13,%14,%15,%16,%17,%18,%19"
#define R32 R20 ",%20,%21,%22,%23,%24,%25,%26,%27,%28,%29,%30,%31"
#define R64 R32 ",%32,%33,%34,%35,%36,%37,%38,%39,%40,%41,%42,%43,%44,%45,%46,%47,%48,%49,%50,%51,%52,%53,%54,%55,%56,%57,%58,%59,%60,%61,%62,%63"

__device__ __forceinline__ void mma_ss128(float (&d)[64], uint64_t a, uint64_t b, int acc) {
  asm volatile("{\n.reg .pred p;\nsetp.ne.b32 p, %66, 0;\n"
               "wgmma.mma_async.sync.aligned.m64n128k16.f32.bf16.bf16 {" R64 "}, %64, %65, p, 1, 1, 0, 1;\n}\n"
               : F16(d, 0), F16(d, 16), F16(d, 32), F16(d, 48) : "l"(a), "l"(b), "r"(acc));
}
__device__ __forceinline__ void mma_ss64(float (&d)[32], uint64_t a, uint64_t b, int acc) {
  asm volatile("{\n.reg .pred p;\nsetp.ne.b32 p, %34, 0;\n"
               "wgmma.mma_async.sync.aligned.m64n64k16.f32.bf16.bf16 {" R32 "}, %32, %33, p, 1, 1, 0, 1;\n}\n"
               : F16(d, 0), F16(d, 16) : "l"(a), "l"(b), "r"(acc));
}
#define R8 "%0,%1,%2,%3,%4,%5,%6,%7"
#define R16 R8 ",%8,%9,%10,%11,%12,%13,%14,%15"
template <int ACC>
__device__ __forceinline__ void mma_qk(float (&d)[32], const uint32_t* a, uint64_t b) {
  asm volatile("{\n.reg .pred p;\nsetp.ne.b32 p, %37, 0;\n"
               "wgmma.mma_async.sync.aligned.m64n64k16.f32.f16.f16 {" R32 "}, {%32,%33,%34,%35}, %36, p, 1, 1, 0;\n}\n"
               : F16(d, 0), F16(d, 16) : "r"(a[0]), "r"(a[1]), "r"(a[2]), "r"(a[3]), "l"(b), "n"(ACC));
}
template <int ACC>
__device__ __forceinline__ void mma_qk(float (&d)[16], const uint32_t* a, uint64_t b) {
  asm volatile("{\n.reg .pred p;\nsetp.ne.b32 p, %21, 0;\n"
               "wgmma.mma_async.sync.aligned.m64n32k16.f32.f16.f16 {" R16 "}, {%16,%17,%18,%19}, %20, p, 1, 1, 0;\n}\n"
               : F16(d, 0) : "r"(a[0]), "r"(a[1]), "r"(a[2]), "r"(a[3]), "l"(b), "n"(ACC));
}
template <int ACC>
__device__ __forceinline__ void mma_qk(uint32_t (&d)[8], const uint32_t* a, uint64_t b) {
  asm volatile("{\n.reg .pred p;\nsetp.ne.b32 p, %13, 0;\n"
               "wgmma.mma_async.sync.aligned.m64n32k16.f16.f16.f16 {" R8 "}, {%8,%9,%10,%11}, %12, p, 1, 1, 0;\n}\n"
               : "+r"(d[0]), "+r"(d[1]), "+r"(d[2]), "+r"(d[3]), "+r"(d[4]), "+r"(d[5]), "+r"(d[6]), "+r"(d[7])
               : "r"(a[0]), "r"(a[1]), "r"(a[2]), "r"(a[3]), "l"(b), "n"(ACC));
}
__device__ __forceinline__ void mma_pv(float (&d)[20], uint32_t a0, uint32_t a1, uint32_t a2, uint32_t a3, uint64_t b) {
  asm volatile("{\n.reg .pred p;\nsetp.ne.b32 p, 1, 0;\n"
               "wgmma.mma_async.sync.aligned.m64n40k16.f32.bf16.bf16 {" R20 "}, {%20,%21,%22,%23}, %24, p, 1, 1, 1;\n}\n"
               : F16(d, 0), F4(d, 16) : "r"(a0), "r"(a1), "r"(a2), "r"(a3), "l"(b));
}

__device__ __forceinline__ void mbar_init(uint32_t mb, uint32_t n) { asm volatile("mbarrier.init.shared::cta.b64 [%0], %1;" ::"r"(mb), "r"(n) : "memory"); }
__device__ __forceinline__ void mbar_wait(uint32_t mb, uint32_t par) {
  asm volatile("{\n.reg .pred p;\n.reg .u32 n;\n"
               "mbarrier.try_wait.parity.shared::cta.b64 p, [%0], %1;\n@p bra.uni DONE;\nmov.u32 n, 0;\n"
               "LOOP:\nmbarrier.try_wait.parity.shared::cta.b64 p, [%0], %1;\nadd.u32 n, n, 1;\n"
               "setp.gt.or.u32 p, n, 2097152, p;\n@!p bra.uni LOOP;\nDONE:\n}" ::"r"(mb), "r"(par) : "memory");
}
template <int NS>
__device__ __forceinline__ void mbar_wait_sleep(uint32_t mb, uint32_t par) {
  asm volatile("{\n.reg .pred p;\n.reg .u32 n;\nmov.u32 n, 0;\n"
               "LOOP:\nmbarrier.test_wait.parity.shared::cta.b64 p, [%0], %1;\nadd.u32 n, n, 1;\n"
               "setp.gt.or.u32 p, n, 2097152, p;\n@p bra.uni DONE;\nnanosleep.u32 %2;\nbra.uni LOOP;\nDONE:\n}" ::"r"(mb), "r"(par), "n"(NS) : "memory");
}
#define OD_SLEEP 300
#define KV_SLEEP 200
__device__ __forceinline__ void mbar_arrive(uint32_t mb) { asm volatile("mbarrier.arrive.shared::cta.b64 _, [%0];" ::"r"(mb) : "memory"); }
__device__ __forceinline__ void mbar_expect(uint32_t mb, uint32_t bytes) { asm volatile("mbarrier.arrive.expect_tx.shared::cta.b64 _, [%0], %1;" ::"r"(mb), "r"(bytes) : "memory"); }
__device__ __forceinline__ void tma_load(uint32_t dst, const CUtensorMap* m, int c0, int c1, uint32_t mb) {
  asm volatile("cp.async.bulk.tensor.2d.shared::cluster.global.mbarrier::complete_tx::bytes [%0], [%1, {%3, %4}], [%2];"
               ::"r"(dst), "l"(m), "r"(mb), "r"(c0), "r"(c1) : "memory");
}
__device__ __forceinline__ void tma_store(const CUtensorMap* m, uint32_t src, int c0, int c1) {
  asm volatile("cp.async.bulk.tensor.2d.global.shared::cta.bulk_group [%0, {%2, %3}], [%1];" ::"l"(m), "r"(src), "r"(c0), "r"(c1) : "memory");
}
__device__ __forceinline__ void bulk_load(uint32_t dst, const void* src, uint32_t bytes, uint32_t mb) {
  asm volatile("cp.async.bulk.shared::cluster.global.mbarrier::complete_tx::bytes [%0], [%1], %2, [%3];"
               ::"r"(dst), "l"(src), "r"(bytes), "r"(mb) : "memory");
}
__device__ __forceinline__ void bulk_store(void* dst, uint32_t src, uint32_t bytes) {
  asm volatile("cp.async.bulk.global.shared::cta.bulk_group [%0], [%1], %2;" ::"l"(dst), "r"(src), "r"(bytes) : "memory");
}
__device__ __forceinline__ void tma_load_mc(uint32_t dst, const CUtensorMap* m, int c0, int c1, uint32_t mb) {
  asm volatile("cp.async.bulk.tensor.2d.shared::cluster.global.mbarrier::complete_tx::bytes.multicast::cluster [%0], [%1, {%3, %4}], [%2], %5;"
               ::"r"(dst), "l"(m), "r"(mb), "r"(c0), "r"(c1), "h"((uint16_t)3) : "memory");
}
__device__ __forceinline__ void mbar_arrive_cluster(uint32_t mb) { asm volatile("mbarrier.arrive.shared::cluster.b64 _, [%0];" ::"r"(mb) : "memory"); }
__device__ __forceinline__ void red_max_shared(uint32_t a, uint32_t v) { asm volatile("red.shared.max.u32 [%0], %1;" ::"r"(a), "r"(v) : "memory"); }
__device__ __forceinline__ void prefetch_map(const CUtensorMap* m) { asm volatile("prefetch.tensormap [%0];" ::"l"(m) : "memory"); }
__device__ __forceinline__ void pace(uint32_t cycles) {
  uint32_t t0, t;
  asm volatile("mov.u32 %0, %%clock;" : "=r"(t0));
  do { __nanosleep(50); asm volatile("mov.u32 %0, %%clock;" : "=r"(t)); } while (t - t0 < cycles);
}
#define ST_PACE 450
__device__ __forceinline__ void fence_async() { asm volatile("fence.proxy.async.shared::cta;" ::: "memory"); }
__device__ __forceinline__ void signal(int idx) {
  asm volatile("fence.acq_rel.gpu;\nred.relaxed.gpu.global.add.u32 [%0], 1;" ::"l"(g_sync + idx * 32) : "memory");
}
__device__ __forceinline__ void poll(int idx, uint32_t target) {
  uint32_t v, n = 0;
  while (true) {
    asm volatile("ld.acquire.gpu.global.u32 %0, [%1];" : "=r"(v) : "l"(g_sync + idx * 32) : "memory");
    if (v >= target || ++n > (1u << 20)) break;
    __nanosleep(40);
  }
  asm volatile("fence.proxy.async.global;" ::: "memory");
}
__device__ __forceinline__ float ex2(float x) { float y; asm("ex2.approx.ftz.f32 %0, %1;" : "=f"(y) : "f"(x)); return y; }
__device__ __forceinline__ float rcp(float x) { float y; asm("rcp.approx.ftz.f32 %0, %1;" : "=f"(y) : "f"(x)); return y; }
__device__ __forceinline__ void stg128(void* p, uint32_t a, uint32_t b, uint32_t c, uint32_t d) {
  asm volatile("st.global.v4.b32 [%0], {%1,%2,%3,%4};" ::"l"(p), "r"(a), "r"(b), "r"(c), "r"(d) : "memory");
}
__device__ __forceinline__ uint32_t pack(float lo, float hi) { uint32_t r; asm("cvt.rn.bf16x2.f32 %0, %1, %2;" : "=r"(r) : "f"(hi), "f"(lo)); return r; }
__device__ __forceinline__ uint32_t packh(float lo, float hi) { uint32_t r; asm("cvt.rn.f16x2.f32 %0, %1, %2;" : "=r"(r) : "f"(hi), "f"(lo)); return r; }
__device__ __forceinline__ void sts128(uint32_t addr, uint32_t a, uint32_t b, uint32_t c, uint32_t d) {
  asm volatile("st.shared.v4.b32 [%0], {%1,%2,%3,%4};" ::"r"(addr), "r"(a), "r"(b), "r"(c), "r"(d) : "memory");
}
__device__ __forceinline__ void stsm4(uint32_t addr, uint32_t a, uint32_t b, uint32_t c, uint32_t d) {
  asm volatile("stmatrix.sync.aligned.m8n8.x4.shared.b16 [%0], {%1,%2,%3,%4};" ::"r"(addr), "r"(a), "r"(b), "r"(c), "r"(d) : "memory");
}
__device__ __forceinline__ void lds128(uint32_t addr, uint32_t& a, uint32_t& b, uint32_t& c, uint32_t& d) {
  asm volatile("ld.shared.v4.b32 {%0,%1,%2,%3}, [%4];" : "=r"(a), "=r"(b), "=r"(c), "=r"(d) : "r"(addr) : "memory");
}

__device__ __forceinline__ uint32_t exp2_h2(uint32_t s, uint32_t cw) {
  uint32_t t, w, y, a, b;
  asm("add.rn.f16x2 %0, %1, %2;" : "=r"(t) : "r"(s), "r"(0x65b665b6u));
  asm("fma.rn.f16x2 %0, %1, %2, %3;" : "=r"(w) : "r"(t), "r"(0xc040c040u), "r"(cw));
  asm("fma.rn.f16x2 %0, %1, %2, %3;" : "=r"(y) : "r"(s), "r"(0x40404040u), "r"(w));
  asm("fma.rn.f16x2 %0, %1, %1, %2;" : "=r"(a) : "r"(y), "r"(0x4ed24ed2u));
  asm("fma.rn.f16x2 %0, %1, %2, %3;" : "=r"(b) : "r"(a), "r"(y), "r"(0x64076408u));
  return __funnelshift_l(t, t, 7) + b;
}

struct Ring {
  uint32_t slot, phase;
  template <int N> __device__ __forceinline__ void next() { if (++slot == N) { slot = 0; phase ^= 1; } }
};

__device__ __forceinline__ void gemm128(float (&acc)[64], uint32_t sb, uint32_t wg, bool lane01, uint32_t gempty, Ring& r, int keep, int pidx) {
  const uint64_t a0 = (uint64_t)(((sb & 0x3ffff) + wg * 8192) >> 4) | (1ull << 16) | (64ull << 32) | (1ull << 62);
  const uint64_t b0 = (uint64_t)(((sb & 0x3ffff) + 32768) >> 4) | (512ull << 16) | (64ull << 32) | (1ull << 62);
#pragma unroll 1
  for (int kc = 0; kc < 16; kc++) {
    mbar_wait(sb + BAR_GFULL + r.slot * 8, r.phase);
    PROF(16 + pidx * 16 + kc);
    const uint64_t off = r.slot * (GSTAGE >> 4);
    wg_fence();
#pragma unroll
    for (int k = 0; k < 4; k++) mma_ss128(acc, a0 + off + k * 2, b0 + off + k * 128, kc | k);
    wg_commit();
    wg_wait<0>();
    if (lane01 && kc < 16 - keep) mbar_arrive_cluster(gempty + r.slot * 8);
    r.next<NG>();
  }
  pin(acc);
}

__device__ __forceinline__ uint32_t quad_head_max(float (&v)[8], uint32_t q) {
  float a[4], b[2];
#pragma unroll
  for (int i = 0; i < 4; i++) {
    const float keep = (q & 1) ? v[4 + i] : v[i], send = (q & 1) ? v[i] : v[4 + i];
    a[i] = keep + __shfl_xor_sync(~0u, send, 1);
  }
#pragma unroll
  for (int i = 0; i < 2; i++) {
    const float keep = (q & 2) ? a[2 + i] : a[i], send = (q & 2) ? a[i] : a[2 + i];
    b[i] = keep + __shfl_xor_sync(~0u, send, 2);
  }
  return max(__float_as_uint(b[0]) & 0x7fffffffu, __float_as_uint(b[1]) & 0x7fffffffu);
}

__device__ __forceinline__ float pow2_scale(float amax, float& inv) {
  const int e = (__float_as_uint(amax) >> 23) & 255;
  const int se = (e == 255 || amax == 0.f) ? 127 : min(max(267 - e, 1), 253);
  inv = __uint_as_float((254 - se) << 23);
  return __uint_as_float(se << 23);
}
template <int NH, int NACC>
__device__ __forceinline__ float rescale_heads(float (&acc)[NACC], uint32_t hsel) {
  float mine = 1.f;
#pragma unroll
  for (int h = 0; h < NH; h++) {
    uint32_t am = 0;
#pragma unroll
    for (int i = 0; i < 16; i++) am = max(am, __float_as_uint(acc[h * 16 + i]) & 0x7fffffffu);
    float inv;
    const float sc = pow2_scale(__uint_as_float(__reduce_max_sync(~0u, am)), inv);
#pragma unroll
    for (int i = 0; i < 16; i++) acc[h * 16 + i] *= sc;
    if (hsel == h) mine = inv;
  }
  return mine;
}
template <int NH, int NACC>
__device__ __forceinline__ uint32_t head_norms(float (&acc)[NACC], uint32_t q4) {
  float nrm[8];
#pragma unroll
  for (int i = 0; i < 8; i++) {
    float n = 0.f;
    if (i < 2 * NH) {
#pragma unroll
      for (int j = 0; j < 4; j++) {
        const float x = acc[(i >> 1) * 16 + j * 4 + (i & 1) * 2], y = acc[(i >> 1) * 16 + j * 4 + (i & 1) * 2 + 1];
        n = fmaf(x, x, fmaf(y, y, n));
      }
    }
    nrm[i] = n;
  }
  return quad_head_max(nrm, q4);
}

template <int NK, int NH, int NACC>
__device__ __forceinline__ void stage_kv(float (&acc)[NACC], uint32_t sb, uint32_t stage, uint32_t warp, uint32_t lane, float* kscale) {
  const uint32_t a = stage + (lane >> 2) * 64 + (((lane ^ (lane >> 3)) & 3) << 4), hsel = (lane & 1) * 2 + ((lane >> 1) & 1);
  uint32_t mx;
  float inv = 1.f;
#pragma unroll 1
  for (int pass = 0;; pass++) {
#pragma unroll
    for (int h = 0; h < NH; h++) {
#pragma unroll
      for (int r = 0; r < 2; r++) {
        const float* x = acc + h * 16 + 2 * r;
        if (h < NK) sts128(a + h * 4096 + (r * 4 + warp) * 512, packh(x[0], x[1]), packh(x[4], x[5]), packh(x[8], x[9]), packh(x[12], x[13]));
        else if (r == 0) sts128(a + h * 4096 + warp * 1024, pack(x[0], x[1]), pack(x[4], x[5]), pack(x[8], x[9]), pack(x[12], x[13]));
        else sts128(a + h * 4096 + warp * 1024 + 512, pack(x[0] * CV, x[1] * CV), pack(x[4] * CV, x[5] * CV), pack(x[8] * CV, x[9] * CV), pack(x[12] * CV, x[13] * CV));
      }
    }
    if (NK > 0 && pass) break;
    mx = head_norms<NH>(acc, lane & 3);
    mx = max(mx, __shfl_xor_sync(~0u, mx, 4));
    mx = max(mx, __shfl_xor_sync(~0u, mx, 8));
    mx = max(mx, __shfl_xor_sync(~0u, mx, 16));
    const float n2 = __uint_as_float(mx);
    if (NK == 0 || !__any_sync(~0u, hsel < NK && !(n2 >= H_LO2 && n2 <= H_HI2))) break;
    inv = rescale_heads<NK>(acc, hsel);
    if (hsel < NK && inv != 1.f) mx = 0x7f800000u;
  }
  fence_async();
  if (lane < 4) {
    red_max_shared(sb + OFF_NRM + hsel * 4, mx);
    if (hsel < NK) kscale[hsel * 128] = inv;
  }
  __syncwarp();
}

__device__ __forceinline__ void load_q(uint32_t (&q)[8], uint32_t addr) {
  lds128(addr, q[0], q[2], q[4], q[6]);
  lds128(addr + 1024, q[1], q[3], q[5], q[7]);
}

#define NSPLIT 2
constexpr uint64_t VUNIT = 1ull - (1ull << 16);

struct AttnCtx { uint32_t sb, qaddr, qswz, gempty; uint64_t d0; __nv_bfloat16* orow; bool lane0, lane01; };

template <bool SAFE>
__device__ __forceinline__ void attention(AttnCtx c, const float* kscale, int hstep, float qinv) {
  constexpr int U = SAFE ? 1 : 8;
  const uint32_t sb = c.sb;
  float s[SAFE ? 32 : 16], o[20];
  uint32_t sh[8], q[8], cw;
  asm volatile("ld.shared.u32 %0, [%1];" : "=r"(cw) : "r"(sb + OFF_CONST) : "memory");
  auto scores = [&](uint64_t kd) {
    mma_qk<0>(s, q, kd);
    mma_qk<1>(s, q + 4, kd + 2);
    if (!SAFE) { mma_qk<0>(sh, q, kd + 128); mma_qk<1>(sh, q + 4, kd + 130); }
    wg_commit();
  };
  load_q(q, c.qaddr + c.qswz);
#pragma unroll
  for (int i = 0; i < (SAFE ? 32 : 16); i++) s[i] = 0.f;
#pragma unroll
  for (int i = 0; i < 8; i++) sh[i] = 0;
  pin(s); pin(sh); pin(q);
  wg_fence();
  scores(c.d0 + ((OFF_K0 - OFF_KV) >> 4));
  mbar_wait(sb + BAR_KFULL, 0);
  wg_wait<0>();
  pin(s); pin(sh);
  PROF(4);
#pragma unroll 1
  for (int h = 0; h < 4; h++) {
#pragma unroll
    for (int i = 0; i < 20; i++) o[i] = 0.f;
    pin(o);
    float m0 = -INFINITY, m1 = -INFINITY;
    const float qf = SAFE ? __shfl_sync(~0u, qinv, (h >> 1) + (h & 1) * 2) : 1.f;
#pragma unroll 1
    for (int j = 0; j < 32; j += U) {
      uint64_t dj = c.d0 + (uint64_t)((j & 7) * 256) * VUNIT;
      asm volatile("" : "+l"(dj));
#pragma unroll
      for (int u = 0; u < U; u++) {
        const int st = j + u;
        const uint64_t vd = dj + u * 256 * VUNIT;
        uint32_t p[16];
        if (u == U - 1) {
          if (st == 31 && h < 3) load_q(q, c.qaddr + ((h + 1) >> 1) * GSTAGE + (c.qswz ^ (((h + 1) & 1) << 6)));
          pin(q);
        }
        if constexpr (SAFE) {
          const float4 kf = __ldcg(reinterpret_cast<const float4*>(kscale + h * hstep * 128 + st * 4));
          const float f[4] = {kf.x, kf.y, kf.z, kf.w};
          float mx0 = m0, mx1 = m1;
#pragma unroll
          for (int i = 0; i < 32; i++) {
            s[i] = s[i] * f[(i >> 2) & 3] * qf;
            if (i & 2) mx1 = fmaxf(mx1, s[i]); else mx0 = fmaxf(mx0, s[i]);
          }
          mx0 = fmaxf(mx0, __shfl_xor_sync(~0u, mx0, 1)); mx1 = fmaxf(mx1, __shfl_xor_sync(~0u, mx1, 1));
          mx0 = fmaxf(mx0, __shfl_xor_sync(~0u, mx0, 2)); mx1 = fmaxf(mx1, __shfl_xor_sync(~0u, mx1, 2));
          const float u0 = mx0 == -INFINITY ? 0.f : mx0, u1 = mx1 == -INFINITY ? 0.f : mx1;
          const float c0 = ex2(m0 - u0), c1 = ex2(m1 - u1);
          m0 = mx0; m1 = mx1;
#pragma unroll
          for (int i = 0; i < 20; i++) o[i] *= (i & 2) ? c1 : c0;
#pragma unroll
          for (int k = 0; k < 4; k++) {
            p[4 * k] = pack(ex2(s[4 * k] - u0), ex2(s[4 * k + 1] - u0));
            p[4 * k + 1] = pack(ex2(s[4 * k + 2] - u1), ex2(s[4 * k + 3] - u1));
            p[4 * k + 2] = pack(ex2(s[4 * k + 16] - u0 + CV_LOG2), ex2(s[4 * k + 17] - u0 + CV_LOG2));
            p[4 * k + 3] = pack(ex2(s[4 * k + 18] - u1 + CV_LOG2), ex2(s[4 * k + 19] - u1 + CV_LOG2));
          }
          pin(p); pin(o);
          wg_fence();
#pragma unroll
          for (int k = 0; k < 4; k++) mma_pv(o, p[4 * k], p[4 * k + 1], p[4 * k + 2], p[4 * k + 3], vd + k * 64 * VUNIT);
        } else {
#pragma unroll
          for (int k = 0; k < 4; k++) {
            p[4 * k] = pack(ex2(s[4 * k]), ex2(s[4 * k + 1]));
            p[4 * k + 1] = pack(ex2(s[4 * k + 2]), ex2(s[4 * k + 3]));
            p[4 * k + 2] = exp2_h2(sh[2 * k], cw);
            p[4 * k + 3] = exp2_h2(sh[2 * k + 1], cw);
            asm volatile("" : "+r"(p[4 * k]), "+r"(p[4 * k + 1]), "+r"(p[4 * k + 2]), "+r"(p[4 * k + 3])::"memory");
            constexpr int KS = 4 / NSPLIT;
            if (k % KS == KS - 1) {
              wg_fence();
#pragma unroll
              for (int kk = k - KS + 1; kk <= k; kk++) mma_pv(o, p[4 * kk], p[4 * kk + 1], p[4 * kk + 2], p[4 * kk + 3], vd + kk * 64 * VUNIT);
              if (k < 3) wg_commit();
            }
          }
        }
        scores(dj + u * 256 + 2048);
        const bool last = st % KSTEPS == KSTEPS - 1;
        if (last) mbar_wait(sb + BAR_KFULL + (((st + 1) & 7) / KSTEPS) * 8, ((st + 1) >> 3) & 1);
        wg_wait<0>();
        if (last && c.lane0) mbar_arrive(sb + BAR_KEMPTY + ((st & 7) / KSTEPS) * 8);
        pin(s); pin(sh); pin(o);
      }
    }
    if (h == 2) {
      fence_async();
      __syncwarp();
      if (c.lane01) { mbar_arrive_cluster(c.gempty); mbar_arrive_cluster(c.gempty + 8); }
    }
    const float i0 = rcp(o[16]), i1 = rcp(o[18]);
    stg128(c.orow, pack(o[0] * i0, o[1] * i0), pack(o[4] * i0, o[5] * i0), pack(o[8] * i0, o[9] * i0), pack(o[12] * i0, o[13] * i0));
    stg128(c.orow + 8 * 1024, pack(o[2] * i1, o[3] * i1), pack(o[6] * i1, o[7] * i1), pack(o[10] * i1, o[11] * i1), pack(o[14] * i1, o[15] * i1));
    c.orow += 32;
    __syncwarp();
    if (c.lane0 && (h & 1)) mbar_arrive(sb + BAR_OD);
    PROF(5 + h);
  }
}

__global__ void __cluster_dims__(2, 1, 1) __launch_bounds__(NTHREADS, 1) fused_kernel(const __grid_constant__ Maps maps) {
  extern __shared__ __align__(1024) uint8_t smem_raw[];
  const uint32_t sb = ((uint32_t)__cvta_generic_to_shared(smem_raw) + 1023) & ~1023u;
  const uint32_t tid = threadIdx.x, lane = tid & 31;
  const uint32_t wg = __shfl_sync(~0u, tid >> 7, 0);
  const int cta = blockIdx.x;
  const bool aux = cta >= NMAIN;
  const int br = (cta >> 6) & 1, rb = (cta >> 3) & 7, hg = cta & 7;
  const int rb1 = cta >> 4, ct1 = cta & 15;
  PROF(0);
  PROF_GT(0);

  if (tid == 512) {
    for (int i = 0; i < NG; i++) mbar_init(sb + BAR_GFULL + i * 8, 1);
    fence_async();
#pragma unroll 1
    for (int i = 0; i < NG; i++) {
      const uint32_t st = sb + i * GSTAGE, fb = sb + BAR_GFULL + i * 8;
      PROF(16 + i);
      if (aux) {
        mbar_expect(fb, 32768 + 8192);
        tma_load(st, &maps.xA, i * 64, (cta - NMAIN) * 512, fb);
        tma_load(st + 16384, &maps.xA, i * 64, (cta - NMAIN) * 512 + 128, fb);
        tma_load(st + 32768, &maps.wk, 0, i * 64, fb);
        tma_load(st + 32768 + 4096, &maps.wv, 0, i * 64, fb);
      } else {
        mbar_expect(fb, GSTAGE);
        tma_load(st + 32768, &maps.wqkv, 1024 + ct1 * 128, i * 64, fb);
        tma_load(st, &maps.xB, i * 64, rb1 * 256, fb);
        tma_load(st + 32768 + 8192, &maps.wqkv, 1024 + ct1 * 128 + 64, i * 64, fb);
        tma_load(st + 16384, &maps.xB, i * 64, rb1 * 256 + 128, fb);
      }
    }
    asm volatile("fence.mbarrier_init.release.cluster;" ::: "memory");
  }
  if (tid == 544) {
    for (int i = 0; i < NG; i++) mbar_init(sb + BAR_GEMPTY + i * 8, aux ? 16 : 32);
    for (int i = 0; i < NKV; i++) { mbar_init(sb + BAR_KFULL + i * 8, 1); mbar_init(sb + BAR_KEMPTY + i * 8, 16); }
    mbar_init(sb + BAR_K0, 1);
    mbar_init(sb + BAR_OD, 16);
    for (int i = 0; i < 4; i++) mbar_init(sb + BAR_ST + i * 8, 4);
    asm volatile("st.shared.u32 [%0], %1;" ::"r"(sb + OFF_CONST), "r"(0x6a136a13u) : "memory");
    asm volatile("st.shared.v4.u32 [%0], {%1,%1,%1,%1};" ::"r"(sb + OFF_NRM), "r"(0) : "memory");
    asm volatile("fence.mbarrier_init.release.cluster;" ::: "memory");
  }
  if (tid < 256) asm volatile("st.shared.u32 [%0], %1;" ::"r"(sb + OFF_ONES + tid * 4), "r"(tid < 128 ? 0x3f803f80u : 0x3f353f35u) : "memory");
  fence_async();
  __syncthreads();
  asm volatile("barrier.cluster.arrive.relaxed.aligned;\nbarrier.cluster.wait.aligned;" ::: "memory");

  if (wg == 4) {
    asm volatile("setmaxnreg.dec.sync.aligned.u32 32;");
    const uint32_t pwarp = __shfl_sync(~0u, (tid >> 5) & 3, 0);
    if (pwarp == 1) {
      if (lane == 0) {
#pragma unroll 1
        for (int pass = 0; pass < (aux ? 2 : 1); pass++) {
#pragma unroll 1
          for (int w = 0; w < 4; w++) {
            mbar_wait_sleep<100>(sb + BAR_ST + w * 8, pass);
            const uint32_t src = sb + OFF_KV + w * 16384 + pass * 8192;
            if (aux) {
              const int key = 32 * SEQ + (cta - NMAIN) * 512 + pass * 256 + w * 64;
              bulk_store(g_K + key * 32, src, 4096);
              bulk_store(g_V + key * 32, src + 4096, 4096);
            } else {
              __nv_bfloat16* dst = (ct1 < 8 ? g_K : g_V) + ((ct1 & 7) * 4 * SEQ + rb1 * 256 + w * 64) * 32;
#pragma unroll 1
              for (int h = 0; h < 4; h++) { PROFX(64 + w * 4 + h); bulk_store(dst + h * SEQ * 32, src + h * 4096, 4096); pace(ST_PACE); }
            }
          }
        }
        uint4 nrm;
        lds128(sb + OFF_NRM, nrm.x, nrm.y, nrm.z, nrm.w);
        g_norm[cta] = nrm;
        asm volatile("cp.async.bulk.commit_group;\ncp.async.bulk.wait_group 0;" ::: "memory");
        PROFX(1);
        signal(SY_KV + (aux ? 8 : (ct1 & 7)));
        PROFX(2);
        if (!aux) poll(SY_KV + (br ? hg : 8), br ? 16 : NAUX);
        PROFX(3);
      }
      __syncwarp();
      if (!aux) {
        uint4 n = __ldcg(g_norm + (br ? (lane & 7) * 16 + (lane & 8) + hg : NMAIN + (lane & 3)));
        if (!br) { n.x = (lane & 8) ? n.y : n.x; n.y = n.z = n.w = n.x; }
#pragma unroll
        for (int o = 1; o < 8; o *= 2) {
          n.x = max(n.x, __shfl_xor_sync(~0u, n.x, o)); n.y = max(n.y, __shfl_xor_sync(~0u, n.y, o));
          n.z = max(n.z, __shfl_xor_sync(~0u, n.z, o)); n.w = max(n.w, __shfl_xor_sync(~0u, n.w, o));
        }
        const uint32_t mine = (lane & 2) ? ((lane & 1) ? n.w : n.z) : ((lane & 1) ? n.y : n.x);
        const float k2 = __uint_as_float(mine), v2 = __uint_as_float(__shfl_xor_sync(~0u, mine, 8));
        const float lim = (v2 >= V_LO2 && v2 <= V_HI2 && k2 <= H_HI2) ? fminf(__fdividef(S_BOUND2, fmaxf(k2, 1e-30f)), H_HI2) : -1.f;
        if (lane < 4) asm volatile("st.shared.f32 [%0], %1;" ::"r"(sb + OFF_QLIM + lane * 4), "f"(lim) : "memory");
        __syncwarp();
        if (lane == 0) {
          const int kvh0 = br ? hg * 4 : 32, hstep = br ? 1 : 0;
          mbar_expect(sb + BAR_K0, 4096);
          bulk_load(sb + OFF_K0, g_K + kvh0 * SEQ * 32, 4096, sb + BAR_K0);
          PROFX(4);
          constexpr int SPH = 32 / KSTEPS, KB = KSTEPS * 4096;
#pragma unroll 1
          for (int t = 0; t <= 4 * SPH; t++) {
            const uint32_t slot = t & (NKV - 1), st = sb + OFF_KV + slot * KB, fb = sb + BAR_KFULL + slot * 8;
            mbar_wait_sleep<KV_SLEEP>(sb + BAR_KEMPTY + slot * 8, ((t / NKV) & 1) ^ 1);
            if (t == 4 * SPH) { mbar_arrive(fb); break; }
            const int hc = kvh0 + (t / SPH) * hstep, key = (t % SPH) * KSTEPS * 64;
            const int hn = kvh0 + min((t + 1) / SPH, 3) * hstep;
            mbar_expect(fb, KVSTAGE);
            bulk_load(st, g_V + (hc * SEQ + key) * 32, KB, fb);
            bulk_load(st + 32768, g_K + (hc * SEQ + key + 64) * 32, KB - 4096, fb);
            bulk_load(st + 32768 + KB - 4096, g_K + (hn * SEQ + ((t + 1) % SPH) * KSTEPS * 64) * 32, 4096, fb);
          }
        }
      }
    }
    if (tid == 576 && !aux) {
      prefetch_map(br ? &maps.woB : &maps.woA); prefetch_map(&maps.o); prefetch_map(&maps.out);
      if (!br) { prefetch_map(&maps.xA); prefetch_map(&maps.wq); }
#pragma unroll 1
      for (int half = 0; half < 2; half++) {
        mbar_wait_sleep<OD_SLEEP>(sb + BAR_OD, half);
        signal(SY_O + (br * 8 + rb) * 2 + half);
      }
    }
    if (tid == 512) {
      Ring g{0, 0};
      if (aux) {
#pragma unroll 1
        for (int i = NG; i < 32; i++) {
          const uint32_t st = sb + g.slot * GSTAGE, fb = sb + BAR_GFULL + g.slot * 8;
          mbar_wait(sb + BAR_GEMPTY + g.slot * 8, g.phase);
          mbar_expect(fb, 32768 + 8192);
          tma_load(st, &maps.xA, (i & 15) * 64, (cta - NMAIN) * 512 + (i >> 4) * 256, fb);
          tma_load(st + 16384, &maps.xA, (i & 15) * 64, (cta - NMAIN) * 512 + (i >> 4) * 256 + 128, fb);
          tma_load(st + 32768, &maps.wk, 0, (i & 15) * 64, fb);
          tma_load(st + 32768 + 4096, &maps.wv, 0, (i & 15) * 64, fb);
          g.next<NG>();
        }
      } else {
#pragma unroll 1
        for (int i = NG; i < 32; i++) {
          const uint32_t st = sb + g.slot * GSTAGE, fb = sb + BAR_GFULL + g.slot * 8;
          const bool p1 = i < 16;
          const CUtensorMap* mx = (p1 || br) ? &maps.xB : &maps.xA;
          const CUtensorMap* mw = (p1 || br) ? &maps.wqkv : &maps.wq;
          const int row = (p1 ? rb1 : rb) * 256, col = p1 ? 1024 + ct1 * 128 : hg * 128, k = (i & 15) * 64;
          mbar_wait(sb + BAR_GEMPTY + g.slot * 8, g.phase);
          PROF(16 + i);
          mbar_expect(fb, GSTAGE);
          tma_load_mc(st + (cta & 1) * 16384, mx, k, row + (cta & 1) * 128, fb);
          tma_load(st + 32768, mw, col, k, fb);
          tma_load(st + 32768 + 8192, mw, col + 64, k, fb);
          g.next<NG>();
        }
        const CUtensorMap* mw = br ? &maps.woB : &maps.woA;
#pragma unroll 1
        for (int i = 0; i < 16; i++) {
          const uint32_t st = sb + g.slot * GSTAGE, fb = sb + BAR_GFULL + g.slot * 8;
          const int k = ((i & 7) * 2 + (i >> 3)) * 64;
          if (i == 0) mbar_wait_sleep<1000>(sb + BAR_GEMPTY, 0);
          if ((i & 7) == 0) poll(SY_O + (br * 8 + rb) * 2 + (i >> 3), 8);
          if (i == NG) mbar_wait_sleep<100>(sb + BAR_GEMPTY + g.slot * 8, g.phase);
          mbar_wait(sb + BAR_GEMPTY + g.slot * 8, g.phase);
          PROF(48 + i);
          mbar_expect(fb, GSTAGE);
          tma_load_mc(st + (cta & 1) * 16384, &maps.o, k, br * SEQ + rb * 256 + (cta & 1) * 128, fb);
          tma_load(st + 32768, mw, hg * 128, k, fb);
          tma_load(st + 32768 + 8192, mw, hg * 128 + 64, k, fb);
          g.next<NG>();
        }
        PROF_DUMP();
        __threadfence();
        if (atomicAdd(g_sync + SY_DONE * 32, 1) == NMAIN - 1) {
#pragma unroll 1
          for (int i = 0; i < SY_N; i++) g_sync[i * 32] = 0;
        }
      }
    }
  } else {
    asm volatile("setmaxnreg.inc.sync.aligned.u32 112;");
    const uint32_t warp = (tid >> 5) & 3, gq = lane >> 2, q4 = lane & 3;
    const bool lane0 = lane == 0;
    const uint32_t hsel = (q4 & 1) * 2 + (q4 >> 1);
    Ring g{0, 0};
    if (aux) {
      const uint64_t a0 = (uint64_t)(((sb & 0x3ffff) + wg * 8192) >> 4) | (1ull << 16) | (64ull << 32) | (1ull << 62);
      const uint64_t b0 = (uint64_t)(((sb & 0x3ffff) + 32768) >> 4) | (256ull << 16) | (32ull << 32) | (2ull << 62);
#pragma unroll 1
      for (int pass = 0; pass < 2; pass++) {
        float acc[32];
#pragma unroll
        for (int i = 0; i < 32; i++) acc[i] = 0.f;
        pin(acc);
#pragma unroll 1
        for (int kc = 0; kc < 16; kc++) {
          mbar_wait(sb + BAR_GFULL + g.slot * 8, g.phase);
          const uint64_t off = g.slot * (GSTAGE >> 4);
          wg_fence();
#pragma unroll
          for (int k = 0; k < 4; k++) mma_ss64(acc, a0 + off + k * 2, b0 + off + k * 64, 1);
          wg_commit();
          wg_wait<0>();
          if (lane0) mbar_arrive(sb + BAR_GEMPTY + g.slot * 8);
          g.next<NG>();
        }
        pin(acc);
        stage_kv<1, 2>(acc, sb, sb + OFF_KV + wg * 16384 + pass * 8192, warp, lane, g_kscale + 32 * 128 + (cta - NMAIN) * 32 + pass * 16 + wg * 4 + warp);
        if (lane0) mbar_arrive(sb + BAR_ST + wg * 8);
      }
    } else {
      bool exact = true;
      float qinv = 1.f;
      uint32_t gempty;
      const bool lane01 = lane < 2;
      asm("mapa.shared::cluster.u32 %0, %1, %2;" : "=r"(gempty) : "r"(sb + BAR_GEMPTY), "r"(lane & 1));
      const uint32_t stash = sb + wg * 8192 + warp * 2048;
      const uint32_t srow = (lane & 7) + ((lane >> 3) & 1) * 8;
      {
        float acc[64];
#pragma unroll
        for (int i = 0; i < 64; i++) acc[i] = 0.f;
        pin(acc);
        gemm128(acc, sb, wg, lane01, gempty, g, 0, 0);
        PROF(1);
        if (ct1 < 8) stage_kv<4, 4>(acc, sb, sb + OFF_KV + wg * 16384, warp, lane, g_kscale + ct1 * 512 + rb1 * 16 + wg * 4 + warp);
        else stage_kv<0, 4>(acc, sb, sb + OFF_KV + wg * 16384, warp, lane, nullptr);
        if (lane0) mbar_arrive(sb + BAR_ST + wg * 8);
        PROF(2);
        gemm128(acc, sb, wg, lane01, gempty, g, 2, 1);
        PROF(3);
#pragma unroll
        for (int i = 0; i < 64; i++) acc[i] *= QSCALE;
#pragma unroll 1
        for (int pass = 0;; pass++) {
#pragma unroll
          for (int j = 0; j < 16; j += 2)
            stsm4(stash + (j >> 3) * GSTAGE + srow * 128 + ((((j & 7) + (lane >> 4)) ^ (lane & 7)) << 4),
                  packh(acc[4 * j], acc[4 * j + 1]), packh(acc[4 * j + 2], acc[4 * j + 3]),
                  packh(acc[4 * j + 4], acc[4 * j + 5]), packh(acc[4 * j + 6], acc[4 * j + 7]));
          if (pass) break;
          const float qn = __uint_as_float(head_norms<4>(acc, q4));
          mbar_wait(sb + BAR_K0, 0);
          float lim;
          asm volatile("ld.shared.f32 %0, [%1];" : "=f"(lim) : "r"(sb + OFF_QLIM + hsel * 4) : "memory");
          uint32_t any;
          asm volatile("{\n.reg .pred p, r;\nsetp.ne.u32 p, %2, 0;\nbarrier.red.or.pred r, %1, 128, p;\nselp.u32 %0, 1, 0, r;\n}"
                       : "=r"(any) : "r"(wg + 1), "r"(qn <= lim ? 0u : 1u) : "memory");
          exact = __any_sync(~0u, any);
          if (!exact) break;
          qinv = rescale_heads<4>(acc, hsel);
        }
        __syncwarp();
      }
      {
        AttnCtx c;
        c.sb = sb; c.qaddr = stash + gq * 128; c.qswz = (q4 ^ gq) << 4; c.gempty = gempty;
        c.d0 = maps.kvdesc + (((sb & 0x3ffff) + OFF_KV) >> 4);
        c.orow = g_O + (size_t)(br * SEQ + rb * 256 + wg * 64 + warp * 16 + gq) * 1024 + hg * 128 + q4 * 8;
        c.lane0 = lane0; c.lane01 = lane01;
        if (__any_sync(~0u, exact)) attention<true>(c, g_kscale + (br ? hg * 4 : 32) * 128, br, qinv);
        else attention<false>(c, nullptr, 0, 1.f);
      }
      {
        float acc[64];
#pragma unroll
        for (int i = 0; i < 64; i++) acc[i] = 0.f;
        pin(acc);
        gemm128(acc, sb, wg, lane01, gempty, g, NG, 2);
        PROF(9);
        const uint32_t stage = sb + OFF_KV + (wg * 4 + warp) * 4096;
#pragma unroll
        for (int j = 0; j < 16; j += 2) {
          stsm4(stage + (j >> 3) * 2048 + srow * 128 + ((((j & 7) + (lane >> 4)) ^ (lane & 7)) << 4),
                pack(acc[4 * j], acc[4 * j + 1]), pack(acc[4 * j + 2], acc[4 * j + 3]),
                pack(acc[4 * j + 4], acc[4 * j + 5]), pack(acc[4 * j + 6], acc[4 * j + 7]));
        }
        fence_async();
        __syncwarp();
        if (lane0) {
          const int row = rb * 256 + wg * 64 + warp * 16, col = br * 1024 + hg * 128;
          tma_store(&maps.out, stage, col, row);
          tma_store(&maps.out, stage + 2048, col + 64, row);
          asm volatile("cp.async.bulk.commit_group;\ncp.async.bulk.wait_group.read 0;" ::: "memory");
        }
        PROF(10);
        PROF_DUMP();
      }
    }
  }
}

typedef CUresult (*EncodeFn)(CUtensorMap*, CUtensorMapDataType, cuuint32_t, void*, const cuuint64_t*, const cuuint64_t*,
                             const cuuint32_t*, const cuuint32_t*, CUtensorMapInterleave, CUtensorMapSwizzle,
                             CUtensorMapL2promotion, CUtensorMapFloatOOBfill);

void make_map(EncodeFn enc, CUtensorMap* m, void* p, uint64_t cols, uint64_t rows, uint32_t bc, uint32_t brows, CUtensorMapSwizzle sw) {
  cuuint64_t dims[2] = {cols, rows}, strides[1] = {cols * 2};
  cuuint32_t box[2] = {bc, brows}, es[2] = {1, 1};
  enc(m, CU_TENSOR_MAP_DATA_TYPE_BFLOAT16, 2, p, dims, strides, box, es, CU_TENSOR_MAP_INTERLEAVE_NONE, sw,
      CU_TENSOR_MAP_L2_PROMOTION_L2_128B, CU_TENSOR_MAP_FLOAT_OOB_FILL_NONE);
}

}

extern "C" void kernel_launch(void* const* d_in, const int* in_sizes, int n_in, void* d_out, int out_size) {
  static EncodeFn enc = nullptr;
  static void* o_ptr = nullptr;
  if (!enc) {
    void* fn = nullptr;
    cudaDriverEntryPointQueryResult qr;
    cudaGetDriverEntryPoint("cuTensorMapEncodeTiled", &fn, cudaEnableDefault, &qr);
    enc = (EncodeFn)fn;
    cudaGetSymbolAddress(&o_ptr, g_O);
    cudaFuncSetAttribute(fused_kernel, cudaFuncAttributeMaxDynamicSharedMemorySize, SMEM_BYTES);
  }
  Maps m;
  const CUtensorMapSwizzle S128 = CU_TENSOR_MAP_SWIZZLE_128B, S64 = CU_TENSOR_MAP_SWIZZLE_64B;
  make_map(enc, &m.xA, d_in[0], 1024, SEQ, 64, 128, S128);
  make_map(enc, &m.wq, d_in[1], 1024, 1024, 64, 64, S128);
  make_map(enc, &m.wk, d_in[2], 32, 1024, 32, 64, S64);
  make_map(enc, &m.wv, d_in[3], 32, 1024, 32, 64, S64);
  make_map(enc, &m.woA, d_in[4], 1024, 1024, 64, 64, S128);
  make_map(enc, &m.xB, d_in[5], 1024, SEQ, 64, 128, S128);
  make_map(enc, &m.wqkv, d_in[6], 3072, 1024, 64, 64, S128);
  make_map(enc, &m.woB, d_in[7], 1024, 1024, 64, 64, S128);
  make_map(enc, &m.o, o_ptr, 1024, 2 * SEQ, 64, 128, S128);
  make_map(enc, &m.out, d_out, 2048, SEQ, 64, 16, S128);
  m.kvdesc = ((uint64_t)((OFF_ONES - OFF_KV) >> 4) << 16) | (32ull << 32) | (2ull << 62);
  fused_kernel<<<NCTA, NTHREADS, SMEM_BYTES>>>(m);
}
```

```cpp
#include <cuda_runtime.h>
#include <cuda_bf16.h>
#include <cuda.h>
#include <stdint.h>
#include <type_traits>

namespace {

constexpr int SEQ = 2048;
constexpr int NMAIN = 128, NAUX = 4, NCTA = NMAIN + NAUX;
constexpr int NTHREADS = 640;
constexpr int NG = 3;
constexpr int GSTAGE = 49152;
constexpr int NKV = 2, KB = 16384;
constexpr int OFF_KV = NG * GSTAGE;
constexpr int OFF_Q3 = OFF_KV + 4 * KB;
constexpr int OFF_ONES = OFF_Q3 + 16384;
constexpr int OFF_BAR = OFF_ONES + 1536;
constexpr int BAR_GFULL = OFF_BAR, BAR_GEMPTY = BAR_GFULL + 32;
constexpr int BAR_KFULL = BAR_GEMPTY + 32, BAR_KEMPTY = BAR_KFULL + 8 * NKV;
constexpr int BAR_K0 = BAR_KEMPTY + 8 * NKV;
constexpr int BAR_ST = BAR_K0 + 8;
constexpr int BAR_OD = BAR_ST + 32;
constexpr int BAR_GO = BAR_OD + 8;
constexpr int OFF_QLIM = BAR_GO + 8;
constexpr int OFF_CONST = OFF_QLIM + 16;
constexpr int OFF_SB = OFF_BAR + 192;
constexpr int OFF_NRM = OFF_BAR + 240;
constexpr int OFF_QINV = OFF_BAR + 256;
constexpr int SMEM_BYTES = OFF_BAR + 512 + 1024;

constexpr float QSCALE = 0.17677669529663687f * 1.4426950408889634f;
constexpr float S_BOUND2 = 56.f * 56.f * 0.97f;
constexpr float CV = 0.70703125f;
constexpr float CV_LOG2 = 0.50015411f;
constexpr uint32_t H_HI = 0x6f53;
constexpr float H_HI2 = 60000.f;
constexpr float V_LO2 = 8.2718061e-25f;
constexpr float V_HI2 = 1.2089258e24f;

struct Maps { CUtensorMap xA, xB, wq, wqkv, wk, wv, woA, woB, o, out; };

constexpr int SY_KV = 0, SY_O = 9, SY_KV2 = 41, SY_DONE = 49, SY_N = 50;
struct Scratch {
  __nv_bfloat16 O[2 * SEQ * 1024];
  __nv_bfloat16 V[33 * SEQ * 32];
  __nv_bfloat16 K[(33 * SEQ + 128) * 32];
  uint4 norm[NCTA];
  float kscale[33 * 128];
  uint32_t pad[16];
  uint32_t sync[SY_N * 32];
};
__device__ __align__(1024) Scratch g_scratch;

__device__ __forceinline__ void wg_fence() { asm volatile("wgmma.fence.sync.aligned;" ::: "memory"); }
__device__ __forceinline__ void wg_commit() { asm volatile("wgmma.commit_group.sync.aligned;" ::: "memory"); }
template <int N> __device__ __forceinline__ void wg_wait() { asm volatile("wgmma.wait_group.sync.aligned %0;" ::"n"(N) : "memory"); }
template <int N> __device__ __forceinline__ void pin(float (&d)[N]) {
#pragma unroll
  for (int i = 0; i < N; i++) asm volatile("" : "+f"(d[i])::"memory");
}
template <int N> __device__ __forceinline__ void pin(uint32_t (&d)[N]) {
#pragma unroll
  for (int i = 0; i < N; i++) asm volatile("" : "+r"(d[i])::"memory");
}
#define F4(a, i) "+f"(a[i]), "+f"(a[i + 1]), "+f"(a[i + 2]), "+f"(a[i + 3])
#define F16(a, i) F4(a, i), F4(a, i + 4), F4(a, i + 8), F4(a, i + 12)
#define R20 "%0,%1,%2,%3,%4,%5,%6,%7,%8,%9,%10,%11,%12,%13,%14,%15,%16,%17,%18,%19"
#define R32 R20 ",%20,%21,%22,%23,%24,%25,%26,%27,%28,%29,%30,%31"
#define R64 R32 ",%32,%33,%34,%35,%36,%37,%38,%39,%40,%41,%42,%43,%44,%45,%46,%47,%48,%49,%50,%51,%52,%53,%54,%55,%56,%57,%58,%59,%60,%61,%62,%63"

__device__ __forceinline__ void mma_ss(float (&d)[64], uint64_t a, uint64_t b, int acc) {
  asm volatile("{\n.reg .pred p;\nsetp.ne.b32 p, %66, 0;\n"
               "wgmma.mma_async.sync.aligned.m64n128k16.f32.bf16.bf16 {" R64 "}, %64, %65, p, 1, 1, 0, 1;\n}\n"
               : F16(d, 0), F16(d, 16), F16(d, 32), F16(d, 48) : "l"(a), "l"(b), "r"(acc));
}
__device__ __forceinline__ void mma_ss(float (&d)[32], uint64_t a, uint64_t b, int acc) {
  asm volatile("{\n.reg .pred p;\nsetp.ne.b32 p, %34, 0;\n"
               "wgmma.mma_async.sync.aligned.m64n64k16.f32.bf16.bf16 {" R32 "}, %32, %33, p, 1, 1, 0, 1;\n}\n"
               : F16(d, 0), F16(d, 16) : "l"(a), "l"(b), "r"(acc));
}
#define R12 "%0,%1,%2,%3,%4,%5,%6,%7,%8,%9,%10,%11"
#define U4(a, i) "+r"(a[i]), "+r"(a[i + 1]), "+r"(a[i + 2]), "+r"(a[i + 3])
template <int ACC>
__device__ __forceinline__ void mma_qk(float (&d)[12], uint64_t a, uint64_t b) {
  asm volatile("{\n.reg .pred p;\nsetp.ne.b32 p, %14, 0;\n"
               "wgmma.mma_async.sync.aligned.m64n24k16.f32.f16.f16 {" R12 "}, %12, %13, p, 1, 1, 0, 0;\n}\n"
               : F4(d, 0), F4(d, 4), F4(d, 8) : "l"(a), "l"(b), "n"(ACC));
}
template <int ACC>
__device__ __forceinline__ void mma_qk(float (&d)[20], uint64_t a, uint64_t b) {
  asm volatile("{\n.reg .pred p;\nsetp.ne.b32 p, %22, 0;\n"
               "wgmma.mma_async.sync.aligned.m64n40k16.f32.f16.f16 {" R20 "}, %20, %21, p, 1, 1, 0, 0;\n}\n"
               : F16(d, 0), F4(d, 16) : "l"(a), "l"(b), "n"(ACC));
}
template <int ACC>
__device__ __forceinline__ void mma_qk(float (&d)[24], uint64_t a, uint64_t b) {
  asm volatile("{\n.reg .pred p;\nsetp.ne.b32 p, %26, 0;\n"
               "wgmma.mma_async.sync.aligned.m64n48k16.f32.f16.f16 {" R20 ",%20,%21,%22,%23}, %24, %25, p, 1, 1, 0, 0;\n}\n"
               : F16(d, 0), F4(d, 16), F4(d, 20) : "l"(a), "l"(b), "n"(ACC));
}
template <int ACC>
__device__ __forceinline__ void mma_qk(uint32_t (&d)[20], uint64_t a, uint64_t b) {
  asm volatile("{\n.reg .pred p;\nsetp.ne.b32 p, %22, 0;\n"
               "wgmma.mma_async.sync.aligned.m64n80k16.f16.f16.f16 {" R20 "}, %20, %21, p, 1, 1, 0, 0;\n}\n"
               : U4(d, 0), U4(d, 4), U4(d, 8), U4(d, 12), U4(d, 16) : "l"(a), "l"(b), "n"(ACC));
}
__device__ __forceinline__ void mma_pv(float (&d)[20], uint32_t a0, uint32_t a1, uint32_t a2, uint32_t a3, uint64_t b) {
  asm volatile("{\n.reg .pred p;\nsetp.ne.b32 p, 1, 0;\n"
               "wgmma.mma_async.sync.aligned.m64n40k16.f32.bf16.bf16 {" R20 "}, {%20,%21,%22,%23}, %24, p, 1, 1, 1;\n}\n"
               : F16(d, 0), F4(d, 16) : "r"(a0), "r"(a1), "r"(a2), "r"(a3), "l"(b));
}

__device__ __forceinline__ bool elect_one() {
  uint32_t p;
  asm volatile("{\n.reg .pred p;\nelect.sync _|p, 0xffffffff;\nselp.u32 %0, 1, 0, p;\n}" : "=r"(p));
  return p;
}
__device__ __forceinline__ void mbar_init(uint32_t mb, uint32_t n) { asm volatile("mbarrier.init.shared::cta.b64 [%0], %1;" ::"r"(mb), "r"(n) : "memory"); }
__device__ __forceinline__ void mbar_wait(uint32_t mb, uint32_t par) {
  asm volatile("{\n.reg .pred p;\n.reg .u32 n;\n"
               "mbarrier.try_wait.parity.shared::cta.b64 p, [%0], %1;\n@p bra.uni DONE;\nmov.u32 n, 0;\n"
               "LOOP:\nmbarrier.try_wait.parity.shared::cta.b64 p, [%0], %1;\nadd.u32 n, n, 1;\n"
               "setp.gt.or.u32 p, n, 2097152, p;\n@!p bra.uni LOOP;\nDONE:\n}" ::"r"(mb), "r"(par) : "memory");
}
__device__ __forceinline__ void mbar_wait_hint(uint32_t mb, uint32_t par) {
  asm volatile("{\n.reg .pred p;\n.reg .u32 n;\nmov.u32 n, 0;\n"
               "LOOP:\nmbarrier.try_wait.parity.shared::cta.b64 p, [%0], %1, 20000;\nadd.u32 n, n, 1;\n"
               "setp.gt.or.u32 p, n, 65536, p;\n@!p bra.uni LOOP;\n}" ::"r"(mb), "r"(par) : "memory");
}
template <int NS>
__device__ __forceinline__ void mbar_wait_sleep(uint32_t mb, uint32_t par) {
  asm volatile("{\n.reg .pred p;\n.reg .u32 n;\nmov.u32 n, 0;\n"
               "LOOP:\nmbarrier.test_wait.parity.shared::cta.b64 p, [%0], %1;\nadd.u32 n, n, 1;\n"
               "setp.gt.or.u32 p, n, 1048576, p;\n@p bra.uni DONE;\nnanosleep.u32 %2;\nbra.uni LOOP;\nDONE:\n}" ::"r"(mb), "r"(par), "n"(NS) : "memory");
}
__device__ __forceinline__ void mbar_arrive(uint32_t mb) { asm volatile("mbarrier.arrive.shared::cta.b64 _, [%0];" ::"r"(mb) : "memory"); }
__device__ __forceinline__ void mbar_expect(uint32_t mb, uint32_t bytes) { asm volatile("mbarrier.arrive.expect_tx.shared::cta.b64 _, [%0], %1;" ::"r"(mb), "r"(bytes) : "memory"); }
__device__ __forceinline__ void tma_load(uint32_t dst, const CUtensorMap* m, int c0, int c1, uint32_t mb) {
  asm volatile("cp.async.bulk.tensor.2d.shared::cluster.global.mbarrier::complete_tx::bytes [%0], [%1, {%3, %4}], [%2];"
               ::"r"(dst), "l"(m), "r"(mb), "r"(c0), "r"(c1) : "memory");
}
__device__ __forceinline__ void tma_store(const CUtensorMap* m, uint32_t src, int c0, int c1) {
  asm volatile("cp.async.bulk.tensor.2d.global.shared::cta.bulk_group [%0, {%2, %3}], [%1];" ::"l"(m), "r"(src), "r"(c0), "r"(c1) : "memory");
}
__device__ __forceinline__ void bulk_load(uint32_t dst, const void* src, uint32_t bytes, uint32_t mb) {
  asm volatile("cp.async.bulk.shared::cluster.global.mbarrier::complete_tx::bytes [%0], [%1], %2, [%3];"
               ::"r"(dst), "l"(src), "r"(bytes), "r"(mb) : "memory");
}
__device__ __forceinline__ void bulk_store(void* dst, uint32_t src, uint32_t bytes) {
  asm volatile("cp.async.bulk.global.shared::cta.bulk_group [%0], [%1], %2;" ::"l"(dst), "r"(src), "r"(bytes) : "memory");
}
__device__ __forceinline__ void tma_load_mc(uint32_t dst, const CUtensorMap* m, int c0, int c1, uint32_t mb) {
  asm volatile("cp.async.bulk.tensor.2d.shared::cluster.global.mbarrier::complete_tx::bytes.multicast::cluster [%0], [%1, {%3, %4}], [%2], %5;"
               ::"r"(dst), "l"(m), "r"(mb), "r"(c0), "r"(c1), "h"((uint16_t)3) : "memory");
}
__device__ __forceinline__ void mbar_arrive_cluster(uint32_t mb) { asm volatile("mbarrier.arrive.shared::cluster.b64 _, [%0];" ::"r"(mb) : "memory"); }
__device__ __forceinline__ void red_max_shared(uint32_t a, uint32_t v) { asm volatile("red.shared.max.u32 [%0], %1;" ::"r"(a), "r"(v) : "memory"); }
__device__ __forceinline__ void prefetch_map(const CUtensorMap* m) { asm volatile("prefetch.tensormap [%0];" ::"l"(m) : "memory"); }
__device__ __forceinline__ void pace(uint32_t cycles) {
  uint32_t t0, t;
  asm volatile("mov.u32 %0, %%clock;" : "=r"(t0));
  do { __nanosleep(50); asm volatile("mov.u32 %0, %%clock;" : "=r"(t)); } while (t - t0 < cycles);
}
__device__ __forceinline__ void fence_async() { asm volatile("fence.proxy.async.shared::cta;" ::: "memory"); }
__device__ __forceinline__ void signal(Scratch* gs, int idx) {
  asm volatile("fence.acq_rel.gpu;\nred.relaxed.gpu.global.add.u32 [%0], 1;" ::"l"(gs->sync + idx * 32) : "memory");
}
__device__ __forceinline__ void poll(Scratch* gs, int idx, uint32_t target) {
  uint32_t v, n = 0;
  while (true) {
    asm volatile("ld.acquire.gpu.global.u32 %0, [%1];" : "=r"(v) : "l"(gs->sync + idx * 32) : "memory");
    if (v >= target || ++n > (1u << 20)) break;
    __nanosleep(100);
  }
  asm volatile("fence.proxy.async.global;" ::: "memory");
}
__device__ __forceinline__ float ex2(float x) { float y; asm("ex2.approx.ftz.f32 %0, %1;" : "=f"(y) : "f"(x)); return y; }
__device__ __forceinline__ float rcp(float x) { float y; asm("rcp.approx.ftz.f32 %0, %1;" : "=f"(y) : "f"(x)); return y; }
__device__ __forceinline__ void stg128(void* p, uint32_t a, uint32_t b, uint32_t c, uint32_t d) {
  asm volatile("st.global.v4.b32 [%0], {%1,%2,%3,%4};" ::"l"(p), "r"(a), "r"(b), "r"(c), "r"(d) : "memory");
}
__device__ __forceinline__ uint32_t pack(float lo, float hi) { uint32_t r; asm("cvt.rn.bf16x2.f32 %0, %1, %2;" : "=r"(r) : "f"(hi), "f"(lo)); return r; }
__device__ __forceinline__ uint32_t packh(float lo, float hi) { uint32_t r; asm("cvt.rn.f16x2.f32 %0, %1, %2;" : "=r"(r) : "f"(hi), "f"(lo)); return r; }
__device__ __forceinline__ void sts128(uint32_t addr, uint32_t a, uint32_t b, uint32_t c, uint32_t d) {
  asm volatile("st.shared.v4.b32 [%0], {%1,%2,%3,%4};" ::"r"(addr), "r"(a), "r"(b), "r"(c), "r"(d) : "memory");
}
__device__ __forceinline__ void stsm4(uint32_t addr, uint32_t a, uint32_t b, uint32_t c, uint32_t d) {
  asm volatile("stmatrix.sync.aligned.m8n8.x4.shared.b16 [%0], {%1,%2,%3,%4};" ::"r"(addr), "r"(a), "r"(b), "r"(c), "r"(d) : "memory");
}
__device__ __forceinline__ void lds128(uint32_t addr, uint32_t& a, uint32_t& b, uint32_t& c, uint32_t& d) {
  asm volatile("ld.shared.v4.b32 {%0,%1,%2,%3}, [%4];" : "=r"(a), "=r"(b), "=r"(c), "=r"(d) : "r"(addr) : "memory");
}

__device__ __forceinline__ void exp2_stage(int stage, uint32_t s, uint32_t cw, uint32_t& t, uint32_t& w, uint32_t& y, uint32_t& p) {
  if (stage == 0) asm volatile("add.rn.f16x2 %0, %1, %2;" : "=r"(t) : "r"(s), "r"(0x64e564e5u));
  if (stage == 1) asm volatile("fma.rn.f16x2 %0, %1, %2, %3;" : "=r"(w) : "r"(t), "r"(0x38603860u), "r"(cw));
  if (stage == 2) asm volatile("fma.rn.f16x2 %0, %1, %2, %3;" : "=r"(y) : "r"(s), "r"(0xb860b860u), "r"(w));
  if (stage == 3) asm volatile("fma.rn.f16x2 %0, %1, %1, %2;" : "=r"(w) : "r"(y), "r"(0x3f4a3f4au));
  if (stage == 4) asm volatile("fma.rn.f16x2 %0, %1, %0, %2;" : "+r"(y) : "r"(w), "r"(0xcc8ccc8du));
  if (stage == 5) asm volatile("{\n.reg .b32 r;\nshf.l.wrap.b32 r, %1, %1, 7;\nadd.u32 %0, r, %2;\n}" : "=r"(p) : "r"(t), "r"(y));
}
#define STEP_CODE \
  M_(10) H_(6,0,1) H_(7,0,0) H_(3,0,1) M_(8) H_(8,0,1) M_(11) P_(5) M_(9) P_(4) H_(7,1,0) H_(9,0,1) M_(1) H_(6,1,1) \
  H_(2,0,0) M_(0) P_(0) H_(3,1,1) H_(0,0,1) H_(8,1,1) H_(1,0,0) M_(2) H_(7,2,0) H_(9,1,1) H_(15,0,1) H_(9,2,1) H_(6,2,1) \
  H_(2,1,0) M_(3) H_(5,0,1) H_(1,1,0) H_(3,2,1) H_(0,1,1) M_(4) H_(4,0,1) P_(1) M_(5) P_(2) H_(8,2,1) H_(14,0,1) \
  H_(7,3,0) M_(19) H_(15,1,1) H_(16,0,1) H_(6,3,1) H_(11,0,0) H_(5,1,1) M_(18) H_(3,3,1) H_(2,2,0) H_(0,2,1) H_(4,1,1) \
  H_(18,0,1) H_(15,2,1) M_(6) H_(1,2,0) M_(7) H_(13,0,0) M_(23) H_(7,4,0) H_(8,3,1) H_(14,1,1) H_(9,3,1) P_(9) \
  H_(19,0,1) M_(16) H_(6,4,1) H_(5,2,1) H_(16,1,1) H_(17,0,0) H_(11,1,0) H_(2,3,0) P_(3) M_(17) H_(3,4,1) H_(0,3,1) \
  H_(4,2,1) H_(1,3,0) H_(12,0,1) H_(6,5,1) H_(18,1,1) H_(7,5,0) F_ V_(3) C_ H_(12,1,1) P_(8) H_(13,1,0) H_(8,4,1) \
  H_(18,2,1) H_(10,0,0) H_(2,4,0) H_(9,4,1) H_(15,3,1) H_(16,2,1) H_(19,1,1) M_(22) H_(5,3,1) H_(11,2,0) H_(17,1,0) \
  H_(0,4,1) H_(14,2,1) M_(21) H_(3,5,1) H_(4,3,1) P_(11) M_(20) H_(8,5,1) H_(1,4,0) H_(14,3,1) H_(10,1,0) P_(10) \
  H_(13,2,0) M_(13) H_(9,5,1) H_(15,4,1) H_(16,3,1) H_(19,2,1) H_(5,4,1) H_(17,2,0) M_(14) M_(12) P_(6) H_(0,5,1) \
  H_(4,4,1) H_(18,3,1) H_(2,5,0) H_(12,2,1) H_(1,5,0) F_ V_(1) V_(0) C_ W0_ H_(11,3,0) H_(14,4,1) H_(13,3,0) H_(10,2,0) \
  H_(16,4,1) H_(15,5,1) H_(19,3,1) H_(5,5,1) M_(15) H_(11,4,0) H_(17,3,0) P_(7) H_(4,5,1) H_(18,4,1) H_(12,3,1) \
  H_(14,5,1) F_ V_(2) V_(6) C_ H_(13,4,0) H_(10,3,0) H_(16,5,1) H_(19,4,1) H_(11,5,0) H_(17,4,0) H_(18,5,1) H_(12,4,1) \
  H_(13,5,0) H_(10,4,0) H_(19,5,1) H_(17,5,0) H_(12,5,1) H_(10,5,0) B0_ F_ V_(5) Q0_ V_(4) Q1_ Q2_ V_(7) Q3_ C_ B1_

constexpr uint32_t seq_of(int phase) {
  uint32_t s = 0;
  for (int i = 0; i < 16; i++) {
    const int g = phase * 16 + i;
    const int slot = phase == 2 ? (i % 4 == 3 ? 3 : (i % 4 + 2) % 3) : (g < 12 ? g % 4 : g % 3);
    s |= slot << (2 * i);
  }
  return s;
}
constexpr uint32_t SEQ_P1 = seq_of(0), SEQ_P2 = seq_of(1), SEQ_P4 = seq_of(2);
constexpr uint32_t phases_after(uint32_t seq, uint32_t ph) {
  for (int i = 0; i < 16; i++) ph ^= 1u << ((seq >> (2 * i)) & 3);
  return ph;
}
constexpr uint32_t PH_P4 = phases_after(SEQ_P2, phases_after(SEQ_P1, 0));

struct Gemm {
  uint32_t sb, sd, wg, gempty, ph;
  bool lane01;
  template <bool FIRST, int NACC>
  __device__ __forceinline__ void issue(float (&acc)[NACC], uint32_t slot) {
    const uint64_t a0 = (uint64_t)((sd + wg * 8192) >> 4) | (1ull << 16) | (64ull << 32) | (1ull << 62);
    const uint64_t b0 = (uint64_t)((sd + 32768) >> 4) | (512ull << 16) | (64ull << 32) | (1ull << 62);
    mbar_wait(sb + BAR_GFULL + slot * 8, ph >> slot);
    ph ^= 1u << slot;
    const uint64_t off = slot * (GSTAGE >> 4);
    wg_fence();
#pragma unroll
    for (int k = 0; k < 4; k++) mma_ss(acc, a0 + off + k * 2, b0 + off + k * 128, !FIRST || k);
    wg_commit();
  }
  __device__ __forceinline__ void release(uint32_t slot) { if (lane01) mbar_arrive_cluster(gempty + slot * 8); }
  template <uint32_t SLOTS, class F>
  __device__ __forceinline__ void first(float (&acc)[64], F shadow) {
    issue<true>(acc, SLOTS & 3);
    shadow();
    wg_wait<0>();
    release(SLOTS & 3);
    pin(acc);
  }
  template <uint32_t SLOTS, int NREL, int TAIL, int NACC>
  __device__ __forceinline__ void rest(float (&acc)[NACC]) {
#pragma unroll 1
    for (int kc = 1; kc < 16 - TAIL; kc++) {
      const uint32_t slot = (SLOTS >> (2 * kc)) & 3;
      issue<false>(acc, slot);
      wg_wait<0>();
      if (kc < NREL) release(slot);
    }
    if (TAIL) {
      if (wg != 0) asm volatile("bar.sync %0, 256;" ::"r"(wg + 5) : "memory");
#pragma unroll
      for (int kc = 16 - TAIL; kc < 16; kc++) issue<false>(acc, (SLOTS >> (2 * kc)) & 3);
      if (wg != 3) asm volatile("bar.arrive %0, 256;" ::"r"(wg + 6) : "memory");
      wg_wait<0>();
    }
    pin(acc);
  }
};

template <bool BF> __device__ __forceinline__ uint32_t fma2(uint32_t a, uint32_t c) {
  uint32_t d;
  if (BF) asm("fma.rn.bf16x2 %0, %1, %1, %2;" : "=r"(d) : "r"(a), "r"(c)); else asm("fma.rn.f16x2 %0, %1, %1, %2;" : "=r"(d) : "r"(a), "r"(c));
  return d;
}
template <bool BF> __device__ __forceinline__ uint32_t add2(uint32_t a, uint32_t b) {
  uint32_t d;
  if (BF) asm("add.rn.bf16x2 %0, %1, %2;" : "=r"(d) : "r"(a), "r"(b)); else asm("add.rn.f16x2 %0, %1, %2;" : "=r"(d) : "r"(a), "r"(b));
  return d;
}
template <bool BF>
__device__ __forceinline__ uint32_t quad_head_max(const uint32_t (&n)[8], uint32_t q) {
  uint32_t x[4];
#pragma unroll
  for (int h = 0; h < 4; h++) x[h] = add2<BF>(__byte_perm(n[2 * h], n[2 * h + 1], 0x5410), __byte_perm(n[2 * h], n[2 * h + 1], 0x7632));
#pragma unroll
  for (int i = 0; i < 2; i++) x[i] = add2<BF>((q & 1) ? x[2 + i] : x[i], __shfl_xor_sync(~0u, (q & 1) ? x[i] : x[2 + i], 1));
  const uint32_t y = add2<BF>((q & 2) ? x[1] : x[0], __shfl_xor_sync(~0u, (q & 2) ? x[0] : x[1], 2));
  const uint32_t m = max(y & 0x7fffu, (y >> 16) & 0x7fffu);
  if (BF) return m << 16;
  float f;
  asm("cvt.f32.f16 %0, %1;" : "=f"(f) : "h"((uint16_t)m));
  return __float_as_uint(f);
}

__device__ __forceinline__ float pow2_scale(float amax, float& inv) {
  const int e = (__float_as_uint(amax) >> 23) & 255;
  const int se = amax == 0.f ? 127 : min(max(267 - e, 1), 253);
  inv = __uint_as_float((254 - se) << 23);
  return __uint_as_float(se << 23);
}
template <int NH>
__device__ __forceinline__ float rescale_heads(float (&acc)[NH * 16], uint32_t hsel) {
  __align__(16) float tmp[NH * 16];
  float mine = 1.f;
#pragma unroll
  for (int i = 0; i < NH * 16; i++) tmp[i] = acc[i];
#pragma unroll 1
  for (int h = 0; h < NH; h++) {
    float x[16], inv;
    uint32_t am = 0;
#pragma unroll
    for (int i = 0; i < 16; i++) {
      x[i] = tmp[h * 16 + i];
      const uint32_t v = __float_as_uint(x[i]) & 0x7fffffffu;
      if (v < 0x7f800000u) am = max(am, v);
    }
    const float sc = pow2_scale(__uint_as_float(__reduce_max_sync(~0u, am)), inv);
#pragma unroll
    for (int i = 0; i < 16; i++) tmp[h * 16 + i] = x[i] * sc;
    if (hsel == h) mine = inv;
  }
#pragma unroll
  for (int i = 0; i < NH * 16; i++) acc[i] = tmp[i];
  return mine;
}

template <int NH>
__device__ __forceinline__ bool out_of_range(const uint32_t (&n)[8]) {
  uint32_t m = 0;
  bool ok = true;
#pragma unroll
  for (int h = 0; h < NH; h++) {
    const uint32_t x = __vmaxu2(n[2 * h], n[2 * h + 1]);
    ok &= __any_sync(~0u, x & 0x7c007c00u);
    m = __vmaxu2(m, x);
  }
  return !ok || __any_sync(~0u, (m + (0x7fffu - H_HI) * 0x10001u) & 0x80008000u);
}
__device__ __forceinline__ uint32_t warp_head_max(uint32_t mx) {
  mx = max(mx, __shfl_xor_sync(~0u, mx, 4));
  mx = max(mx, __shfl_xor_sync(~0u, mx, 8));
  return max(mx, __shfl_xor_sync(~0u, mx, 16));
}

template <bool F16, int NH, class H>
__device__ __forceinline__ void stage_tile(float (&acc)[NH * 16], uint32_t (&n)[8], float& inv, uint32_t a0, uint32_t a1, H hoff, uint32_t lane,
                                           char* gdst = nullptr, bool dup = false) {
  const uint32_t a = (lane >> 2) * 64 + (((lane ^ (lane >> 3)) & 3) << 4);
  inv = 1.f;
#pragma unroll 1
  for (int pass = 0;; pass++) {
#pragma unroll
    for (int i = 0; i < 8; i++) {
      n[i] = 0;
      if (i < 2 * NH) {
        const float* x = acc + (i >> 1) * 16 + 2 * (i & 1);
        uint32_t w[4];
#pragma unroll
        for (int j = 0; j < 4; j++) w[j] = F16 ? packh(x[4 * j], x[4 * j + 1]) : pack(x[4 * j], x[4 * j + 1]);
        const uint32_t ai = a + ((i & 1) ? a1 : a0) + hoff(i >> 1);
        if (NH == 4) sts128(ai, w[0], w[1], w[2], w[3]);
#pragma unroll
        for (int j = 0; j < 4; j++) n[i] = fma2<!F16>(w[j], n[i]);
        if (NH == 4) asm volatile("pmevent 0;" ::: "memory");
        else {
          stg128(gdst + ai, w[0], w[1], w[2], w[3]);
          if (dup) stg128(gdst + SEQ * 64 + ai, w[0], w[1], w[2], w[3]);
        }
      }
    }
    if (!F16 || pass || !out_of_range<NH>(n)) break;
    inv = rescale_heads<NH>(acc, (lane & 1) * 2 + ((lane >> 1) & 1));
  }
}
template <bool ISK, int NH>
__device__ __forceinline__ void stage_kv(float (&acc)[NH * 16], uint32_t (&n)[8], float& inv, uint32_t base, uint32_t wg, uint32_t warp, uint32_t lane,
                                         char* gdst = nullptr, bool dup = false) {
  const uint32_t hf = wg & 1;
  const float c0 = ISK ? QSCALE : warp ? 1.f : CV, c1 = ISK ? QSCALE : CV;
#pragma unroll
  for (int i = 0; i < NH * 16; i++) acc[i] *= (i & 2) ? c1 : c0;
  const uint32_t g0 = !ISK ? hf * 8 + warp * 2 : warp ? hf * 3 + warp - 1 : hf * 5 + 10, g1 = !ISK ? g0 + 1 : hf * 5 + 6 + warp;
  stage_tile<ISK, NH>(acc, n, inv, base + g0 * 512, base + g1 * 512, [](int h) { return h * 8192; }, lane, gdst, dup);
}
template <bool ISK, int NH>
__device__ __forceinline__ void publish_kv(const uint32_t (&n)[8], float inv, uint32_t nrm, uint32_t lane, float* kscale) {
  const uint32_t mx = warp_head_max(quad_head_max<!ISK>(n, lane & 3)), hsel = (lane & 1) * 2 + ((lane >> 1) & 1);
  if (lane < 4 && hsel < NH) {
    red_max_shared(nrm + hsel * 4, ISK && inv != 1.f ? 0x7f800000u : mx);
    if (ISK) kscale[hsel * 128] = inv;
  }
}

constexpr uint64_t VUNIT = 1ull - (1ull << 16);

__device__ __forceinline__ uint32_t fresh_tid() { uint32_t t; asm volatile("mov.u32 %0, %%tid.x;" : "=r"(t)); return t; }
__device__ __forceinline__ uint32_t q_off(uint32_t wg, uint32_t h) {
  return h == 3 ? OFF_Q3 + (wg >> 1) * 8192 + (wg & 1) * 512 : wg * 8192 + (h >> 1) * GSTAGE + (h & 1) * 512;
}
__device__ __forceinline__ uint32_t gempty_addr(uint32_t sb, uint32_t t) {
  uint32_t a;
  asm("mapa.shared::cluster.u32 %0, %1, %2;" : "=r"(a) : "r"(sb + BAR_GEMPTY), "r"(t & 1));
  return a;
}

template <bool EXACT>
__device__ __forceinline__ bool attention(uint32_t sb, uint32_t wg, uint64_t d0, uint64_t k0, uint64_t q0, uint32_t gs0, __nv_bfloat16* otile, const uint32_t (&qn)[8],
                                          const float* kscale, int hstep) {
  using SH = typename std::conditional<EXACT, float, uint32_t>::type;
  constexpr int NS = EXACT ? 12 : 24;
  const uint32_t tid = fresh_tid();
  const bool lane0 = (tid & 31) == 0;
  float s[NS], o[20];
  SH sh[20];
  uint32_t cw, cw2;
  asm volatile("ld.shared.v2.u32 {%0, %1}, [%2];" : "=r"(cw), "=r"(cw2) : "r"(sb + OFF_CONST) : "memory");
  uint64_t qd = q0 + (q_off(wg, 0) >> 4);
  const uint64_t q3 = q0 + (q_off(wg, 3) >> 4);
  const uint32_t ge = __shfl_sync(~0u, (tid & 30) ? 0 : gempty_addr(gs0, tid), tid);
  __nv_bfloat16* orow = otile + (((tid >> 5) * 16 + ((tid >> 2) & 7)) * 1024 + (tid & 3) * 8);
  auto turn_wait = [&] { asm volatile("bar.sync %0, 256;" ::"r"(wg + 9) : "memory"); };
  auto turn_pass = [&] { asm volatile("bar.arrive %0, 256;" ::"r"(((wg + 1) & 3) + 9) : "memory"); };
  auto scores = [&](uint64_t ka, uint64_t kb) {
    mma_qk<0>(s, qd, ka); mma_qk<1>(s, qd + 2, ka + 2);
    mma_qk<0>(sh, qd, kb); mma_qk<1>(sh, qd + 2, kb + 2);
    wg_commit();
  };
#pragma unroll
  for (int i = 0; i < NS; i++) s[i] = 0.f;
#pragma unroll
  for (int i = 0; i < 20; i++) sh[i] = 0;
  pin(s); pin(sh);
  if (!EXACT) mbar_wait(sb + BAR_K0, 0);
  wg_fence();
  scores(k0, k0 + 192);
  uint32_t bad = 0;
  if (!EXACT) {
    const uint32_t q4 = tid & 3;
    float lim;
    asm volatile("ld.shared.f32 %0, [%1];" : "=f"(lim) : "r"(sb + OFF_QLIM + ((q4 & 1) * 2 + (q4 >> 1)) * 4) : "memory");
    asm volatile("{\n.reg .pred p, r;\nsetp.ne.u32 p, %2, 0;\nbarrier.red.or.pred r, %1, 128, p;\nselp.u32 %0, 1, 0, r;\n}"
                 : "=r"(bad) : "r"(wg + 1), "r"(__uint_as_float(quad_head_max<false>(qn, q4)) <= lim ? 0u : 1u) : "memory");
  }
  mbar_wait(sb + BAR_KFULL, 0);
  wg_wait<0>();
  pin(s); pin(sh);
  if (!EXACT) {
    if (__any_sync(~0u, bad)) return false;
    if (lane0) mbar_arrive(sb + BAR_KEMPTY + 8);
  }
#pragma unroll 1
  for (int h = 0; h < 4; h++) {
#pragma unroll
    for (int i = 0; i < 20; i++) o[i] = 0.f;
    pin(o);
    const uint64_t qnext = h < 2 ? qd + (h ? (GSTAGE - 512) >> 4 : 32) : q3;
    if constexpr (EXACT) {
      float m0 = -INFINITY, m1 = -INFINITY, qf;
      asm volatile("ld.shared.f32 %0, [%1];" : "=f"(qf) : "r"(sb + OFF_QINV + (tid >> 5) * 16 + h * 4) : "memory");
      float4 kf = __ldcg(reinterpret_cast<const float4*>(kscale + h * hstep * 128));
#pragma unroll 1
      for (int st = 0; st < 32; st++) {
        const float f[4] = {kf.x * qf, kf.y * qf, kf.z * qf, kf.w * qf};
        kf = __ldcg(reinterpret_cast<const float4*>(kscale + h * hstep * 128 + ((st + 1) & 31) * 4));
        float x[32], mx0 = m0, mx1 = m1;
#pragma unroll
        for (int i = 0; i < 32; i++) {
          x[i] = (i < 12 ? s[i] : sh[i - 12]) * f[((i >> 2) + 1) & 3];
          if (i & 2) mx1 = fmaxf(mx1, x[i]); else mx0 = fmaxf(mx0, x[i]);
        }
        mx0 = fmaxf(mx0, __shfl_xor_sync(~0u, mx0, 1)); mx1 = fmaxf(mx1, __shfl_xor_sync(~0u, mx1, 1));
        mx0 = fmaxf(mx0, __shfl_xor_sync(~0u, mx0, 2)); mx1 = fmaxf(mx1, __shfl_xor_sync(~0u, mx1, 2));
        const float u0 = mx0 == -INFINITY ? 0.f : mx0, u1 = mx1 == -INFINITY ? 0.f : mx1;
        const float c0 = ex2(m0 - u0), c1 = ex2(m1 - u1);
        m0 = mx0; m1 = mx1;
#pragma unroll
        for (int i = 0; i < 20; i++) o[i] *= (i & 2) ? c1 : c0;
#pragma unroll
        for (int i = 0; i < 32; i++) {
          const float d = x[i] - ((i & 2) ? u1 : u0);
          x[i] = ex2(i < 12 ? d : d + CV_LOG2);
        }
        uint32_t p[16];
#pragma unroll
        for (int k = 0; k < 4; k++) {
          const int e = k ? 4 * k - 4 : 28;
          p[4 * k] = pack(x[e], x[e + 1]);
          p[4 * k + 1] = pack(x[e + 2], x[e + 3]);
          p[4 * k + 2] = pack(x[4 * k + 12], x[4 * k + 13]);
          p[4 * k + 3] = pack(x[4 * k + 14], x[4 * k + 15]);
        }
        pin(p); pin(o);
        const uint64_t vd = d0 + (uint64_t)((st & 7) * 256) * VUNIT, kd = d0 + 2048 + (((st - 1) >> 1) & 3) * 512;
        if (st == 31) qd = qnext;
        if ((st & 7) == 1) turn_wait();
        wg_fence();
#pragma unroll
        for (int k = 0; k < 4; k++) mma_pv(o, p[4 * k], p[4 * k + 1], p[4 * k + 2], p[4 * k + 3], vd + k * 64 * VUNIT + (k ? 0 : 32 << 16));
        scores(kd + ((st & 1) ? 0 : 96), kd + ((st & 1) ? 192 : 352));
        if ((st & 7) == 1) turn_pass();
        if ((st & 3) == 3) mbar_wait(sb + BAR_KFULL + ((st + 1) & 4) * 2, (st + 1) >> 3);
        wg_wait<0>();
        if ((st & 3) == 0 && lane0) mbar_arrive(sb + BAR_KEMPTY + 8 - (st & 4) * 2);
        pin(s); pin(sh); pin(o);
      }
    } else {
#pragma unroll 1
      for (int it = 0; it < 4; it++) {
        uint64_t dj = d0;
        asm volatile("" : "+l"(dj));
#pragma unroll
        for (int u = 0; u < 4; u++) {
          const uint64_t vd = dj + u * 512 * VUNIT, kd = dj + u * 512 + 2048;
          const uint64_t qa = (u == 3 && it == 3) ? qnext : qd;
          uint32_t p[32] = {}, t[20], w[20], y[20];
          float e[24];
#define H_(c, i, two) exp2_stage(i, sh[c], two ? cw2 : cw, t[c], w[c], y[c], p[c / 10 * 16 + (c % 10 < 8 ? 2 * (c % 10) + 2 - (c & 1) : c % 10 - 8)]);
#define M_(i) asm volatile("ex2.approx.ftz.f32 %0, %1;" : "=f"(e[i]) : "f"(s[i]));
#define P_(j) asm volatile("cvt.rn.bf16x2.f32 %0, %1, %2;" : "=r"(p[j / 6 * 16 + (j % 6) / 2 * 4 + 4 + (j & 1)]) : "f"(e[2 * j + 1]), "f"(e[2 * j]));
#define V_(k) mma_pv(o, p[4 * k], p[4 * k + 1], p[4 * k + 2], p[4 * k + 3], vd + k * 64 * VUNIT + ((k & 3) ? 0 : 32 << 16));
#define Q0_ mma_qk<0>(s, qa, kd);
#define Q1_ mma_qk<1>(s, qa + 2, kd + 2);
#define Q2_ mma_qk<0>(sh, qa, kd + 192);
#define Q3_ mma_qk<1>(sh, qa + 2, kd + 194);
#define B0_ if (u == 0) turn_wait();
#define B1_ if (u == 0) turn_pass();
#define F_ wg_fence();
#define C_ wg_commit();
#define W0_ wg_wait<0>();
          STEP_CODE
          if (u & 1) mbar_wait(sb + BAR_KFULL + (u == 1) * 8, it + (u == 3));
          wg_wait<0>();
          if ((u & 1) && lane0) mbar_arrive(sb + BAR_KEMPTY + (u >> 1) * 8);
          pin(s); pin(sh); pin(o);
        }
      }
      qd = qnext;
    }
    if (h == 2 && ge) {
      mbar_arrive_cluster(ge); mbar_arrive_cluster(ge + 8);
    }
    const float i0 = rcp(o[16]), i1 = rcp(o[18]);
    stg128(orow, pack(o[0] * i0, o[1] * i0), pack(o[4] * i0, o[5] * i0), pack(o[8] * i0, o[9] * i0), pack(o[12] * i0, o[13] * i0));
    stg128(orow + 8 * 1024, pack(o[2] * i1, o[3] * i1), pack(o[6] * i1, o[7] * i1), pack(o[10] * i1, o[11] * i1), pack(o[14] * i1, o[15] * i1));
    asm volatile("add.u64 %0, %0, 64;" : "+l"(orow));
    __syncwarp();
    if (lane0 && (h & 1)) mbar_arrive(sb + BAR_OD);
  }
  return true;
}

__global__ void __cluster_dims__(2, 1, 1) __launch_bounds__(NTHREADS, 1) fused_kernel(Scratch* gs, uint64_t kvdesc, uint64_t k0desc, uint64_t qdesc, const __grid_constant__ Maps maps) {
  extern __shared__ __align__(1024) uint8_t smem_raw[];
  const uint32_t sb = ((uint32_t)__cvta_generic_to_shared(smem_raw) + 1023) & ~1023u;
  const uint32_t tid = threadIdx.x, lane = tid & 31;
  const uint32_t wg = __shfl_sync(~0u, tid >> 7, 0);
  const int cta = blockIdx.x;
  const bool aux = cta >= NMAIN;
  const int br = (cta >> 6) & 1, rb = (cta >> 3) & 7, hg = cta & 7;
  const int rb1 = cta >> 4, ct1 = cta & 15;

  if (tid == 576) { prefetch_map(aux ? &maps.xA : &maps.xB); prefetch_map(aux ? &maps.wk : &maps.wqkv); }
  const bool w16 = wg == 4 && tid < 544;
  if (w16 && elect_one()) {
    for (int i = 0; i < 4; i++) { mbar_init(sb + BAR_GFULL + i * 8, 1); mbar_init(sb + BAR_GEMPTY + i * 8, aux ? 16 : 32); }
    asm volatile("fence.mbarrier_init.release.cluster;" ::: "memory");
  }
  __syncwarp();
  asm volatile("barrier.cluster.arrive.relaxed.aligned;" ::: "memory");
  if (w16) {
    if (elect_one()) {
      const uint32_t fb = sb + BAR_GFULL;
      const int row = aux ? (cta - NMAIN) * 512 : rb1 * 256;
      mbar_expect(fb, aux ? 32768 + 8192 : GSTAGE);
      tma_load(sb + 32768, aux ? &maps.wk : &maps.wqkv, aux ? 0 : 1024 + ct1 * 128, 0, fb);
      tma_load(sb, aux ? &maps.xA : &maps.xB, 0, row, fb);
      tma_load(sb + 32768 + (aux ? 4096 : 8192), aux ? &maps.wv : &maps.wqkv, aux ? 0 : 1088 + ct1 * 128, 0, fb);
      tma_load(sb + 16384, aux ? &maps.xA : &maps.xB, 0, row + 128, fb);
    }
    __syncwarp();
  }
  if (tid == 544) {
    for (int i = 0; i < NKV; i++) { mbar_init(sb + BAR_KFULL + i * 8, 1); mbar_init(sb + BAR_KEMPTY + i * 8, 16); }
    mbar_init(sb + BAR_K0, 2);
    mbar_init(sb + BAR_OD, 16);
    mbar_init(sb + BAR_GO, 1);
    for (int i = 0; i < 4; i++) mbar_init(sb + BAR_ST + i * 8, 4);
    for (int i = 0; i < 4; i++) asm volatile("st.shared.v2.u32 [%0], {%1, %2};" ::"r"(sb + OFF_SB + i * 8), "r"(sb), "r"(i) : "memory");
    asm volatile("st.shared.v2.u32 [%0], {%1, %1};" ::"r"(sb + OFF_CONST), "r"(0xe15ce15cu) : "memory");
    asm volatile("st.shared.v4.u32 [%0], {%1,%1,%1,%1};" ::"r"(sb + OFF_NRM), "r"(0) : "memory");
  }
  if (tid < 384) asm volatile("st.shared.u32 [%0], %1;" ::"r"(sb + OFF_ONES + tid * 4), "r"(tid < 128 ? 0x3f803f80u : 0x3f353f35u) : "memory");
  fence_async();
  __syncthreads();
  asm volatile("barrier.cluster.wait.aligned;" ::: "memory");

  if (wg == 4) {
    asm volatile("setmaxnreg.dec.sync.aligned.u32 32;");
    const uint32_t pwarp = __shfl_sync(~0u, (tid >> 5) & 3, 0);
    if (pwarp == 1) {
      if (elect_one()) {
#pragma unroll 1
        for (int w = 0; w < 4; w++) mbar_wait_sleep<100>(sb + BAR_ST + w * 8, 0);
        uint4 nrm;
        lds128(sb + OFF_NRM, nrm.x, nrm.y, nrm.z, nrm.w);
        gs->norm[cta] = nrm;
        if (aux) signal(gs, SY_KV + 8);
        else {
          __nv_bfloat16* dst = (ct1 < 8 ? gs->K : gs->V) + ((ct1 & 7) * 4 * SEQ + rb1 * 256) * 32;
#pragma unroll 1
          for (int i = 0; i < 16; i++) {
            bulk_store(dst + ((i >> 2) * SEQ + (i & 3) * 64) * 32, sb + OFF_KV + (i & 2) * 16384 + (i >> 2) * 8192 + (i & 1) * 4096, 4096);
            if (i == 3 || i == 15) {
              asm volatile("cp.async.bulk.commit_group;\ncp.async.bulk.wait_group 0;" ::: "memory");
              signal(gs, (i == 3 ? SY_KV : SY_KV2) + (ct1 & 7));
            } else pace(330);
          }
        }
        if (!aux) {
          poll(gs, SY_KV + (br ? hg : 8), br ? 16 : NAUX);
          constexpr int NST = 32;
          const char* kp = reinterpret_cast<const char*>(gs->K) + (br ? hg * 4 : 32) * (SEQ * 64);
          const char* vp = reinterpret_cast<const char*>(gs->V) + (br ? hg * 4 : 32) * (SEQ * 64);
          const uint32_t wrap = br ? 0xffffffffu : SEQ * 64 - 1;
          mbar_expect(sb + BAR_K0, 8192);
          bulk_load(sb + OFF_KV + 4 * KB - 8192, kp, 8192, sb + BAR_K0);
          mbar_wait_sleep<50>(sb + BAR_GO, 0);
#pragma unroll 1
          for (uint32_t t = 0; t < NST; t++) {
            const uint32_t slot = t & 1, st = sb + OFF_KV + slot * KB, fb = sb + BAR_KFULL + slot * 8, off = (t * KB) & wrap;
            mbar_wait_hint(sb + BAR_KEMPTY + slot * 8, (t + 1) / 2 + 1);
            if (t == 6 && br) poll(gs, SY_KV2 + hg, 16);
            const uint32_t kb = t == NST - 1 ? KB - 8192 : KB;
            mbar_expect(fb, KB + kb);
            bulk_load(st, vp + off, KB, fb);
            bulk_load(st + 32768, kp + off + 8192, kb, fb);
          }
          mbar_arrive(sb + BAR_KFULL);
        }
      }
    }
    if (pwarp == 3 && !aux) {
      if (lane == 0) { mbar_wait_sleep<200>(sb + BAR_ST, 0); poll(gs, SY_KV + (br ? hg : 8), br ? 16 : NAUX); }
      __syncwarp();
      uint4 n = __ldcg(gs->norm + (br ? (lane & 7) * 16 + (lane & 8) + hg : NMAIN + (lane & 3)));
      if (!br) { n.x = (lane & 8) ? n.y : n.x; n.y = n.z = n.w = n.x; }
#pragma unroll
      for (int o = 1; o < 8; o *= 2) {
        n.x = max(n.x, __shfl_xor_sync(~0u, n.x, o)); n.y = max(n.y, __shfl_xor_sync(~0u, n.y, o));
        n.z = max(n.z, __shfl_xor_sync(~0u, n.z, o)); n.w = max(n.w, __shfl_xor_sync(~0u, n.w, o));
      }
      const uint32_t mine = (lane & 2) ? ((lane & 1) ? n.w : n.z) : ((lane & 1) ? n.y : n.x);
      const float k2 = __uint_as_float(mine), v2 = __uint_as_float(__shfl_xor_sync(~0u, mine, 8));
      const float lim = (v2 >= V_LO2 && v2 <= V_HI2 && k2 <= H_HI2) ? fminf(__fdividef(S_BOUND2, fmaxf(k2, 1e-30f)), H_HI2) : -1.f;
      if (lane < 4) asm volatile("st.shared.f32 [%0], %1;" ::"r"(sb + OFF_QLIM + lane * 4), "f"(lim) : "memory");
      __syncwarp();
      if (lane == 0) mbar_arrive(sb + BAR_K0);
    }
    if (pwarp == 2 && !aux && elect_one()) {
      prefetch_map(br ? &maps.woB : &maps.woA); prefetch_map(&maps.o); prefetch_map(&maps.out);
      if (!br) { prefetch_map(&maps.xA); prefetch_map(&maps.wq); }
#pragma unroll 1
      for (int half = 0; half < 2; half++) {
        __nanosleep(10000);
        mbar_wait_hint(sb + BAR_OD, half);
        signal(gs, SY_O + (br * 8 + rb) * 2 + half);
      }
    }
    if (pwarp == 0 && elect_one()) {
      if (aux) {
#pragma unroll 1
        for (int i = 1; i < 32; i++) {
          const uint32_t slot = i & 3, st = sb + slot * GSTAGE, fb = sb + BAR_GFULL + slot * 8;
          mbar_wait(sb + BAR_GEMPTY + slot * 8, (i >> 2) + 1);
          mbar_expect(fb, 32768 + 8192);
          tma_load(st, &maps.xA, (i & 15) * 64, (cta - NMAIN) * 512 + (i >> 4) * 256, fb);
          tma_load(st + 16384, &maps.xA, (i & 15) * 64, (cta - NMAIN) * 512 + (i >> 4) * 256 + 128, fb);
          tma_load(st + 32768, &maps.wk, 0, (i & 15) * 64, fb);
          tma_load(st + 32768 + 4096, &maps.wv, 0, (i & 15) * 64, fb);
        }
      } else {
        uint32_t ph = 14;
#pragma unroll 1
        for (int i = 1; i < 32; i++) {
          const bool p1 = i < 16;
          const uint32_t slot = ((p1 ? SEQ_P1 : SEQ_P2) >> (2 * (i & 15))) & 3, st = sb + slot * GSTAGE, fb = sb + BAR_GFULL + slot * 8;
          const CUtensorMap* mx = (p1 || br) ? &maps.xB : &maps.xA;
          const CUtensorMap* mw = (p1 || br) ? &maps.wqkv : &maps.wq;
          const int row = (p1 ? rb1 : rb) * 256, col = p1 ? 1024 + ct1 * 128 : hg * 128, k = (i & 15) * 64;
          mbar_wait(sb + BAR_GEMPTY + slot * 8, ph >> slot);
          ph ^= 1u << slot;
          mbar_expect(fb, GSTAGE);
          tma_load_mc(st + (cta & 1) * 16384, mx, k, row + (cta & 1) * 128, fb);
          tma_load(st + 32768, mw, col, k, fb);
          tma_load(st + 32768 + 8192, mw, col + 64, k, fb);
        }
        mbar_arrive(sb + BAR_GO);
        ph ^= 8;
        const CUtensorMap* mw = br ? &maps.woB : &maps.woA;
#pragma unroll 1
        for (int i = 0; i < 16; i++) {
          const uint32_t slot = (SEQ_P4 >> (2 * i)) & 3, st = sb + slot * GSTAGE, fb = sb + BAR_GFULL + slot * 8;
          const int k = ((i & 7) * 2 + (i >> 3)) * 64;
          if (i == 0) mbar_wait_sleep<1000>(sb + BAR_GEMPTY, ph);
          if ((i & 7) == 0) poll(gs, SY_O + (br * 8 + rb) * 2 + (i >> 3), 8);
          if (i == 3) mbar_wait_hint(sb + BAR_GEMPTY + 24, ph >> 3);
          mbar_wait(sb + BAR_GEMPTY + slot * 8, ph >> slot);
          ph ^= 1u << slot;
          mbar_expect(fb, GSTAGE);
          tma_load_mc(st + (cta & 1) * 16384, &maps.o, k, br * SEQ + rb * 256 + (cta & 1) * 128, fb);
          tma_load(st + 32768, mw, hg * 128, k, fb);
          tma_load(st + 32768 + 8192, mw, hg * 128 + 64, k, fb);
        }
        __threadfence();
        if (atomicAdd(gs->sync + SY_DONE * 32, 1) == NMAIN - 1) {
#pragma unroll 1
          for (int i = 0; i < SY_N; i++) gs->sync[i * 32] = 0;
        }
      }
    }
  } else {
    asm volatile("setmaxnreg.inc.sync.aligned.u32 112;");
    const uint32_t warp = (tid >> 5) & 3;
    const bool lane0 = lane == 0;
    if (aux) {
      const uint64_t a0 = (uint64_t)(((sb & 0x3ffff) + wg * 8192) >> 4) | (1ull << 16) | (64ull << 32) | (1ull << 62);
      const uint64_t b0 = (uint64_t)(((sb & 0x3ffff) + 32768) >> 4) | (256ull << 16) | (32ull << 32) | (2ull << 62);
#pragma unroll 1
      for (int pass = 0; pass < 2; pass++) {
        float acc[32];
#pragma unroll
        for (int i = 0; i < 32; i++) acc[i] = 0.f;
        pin(acc);
#pragma unroll 1
        for (int kc = 0; kc < 16; kc++) {
          const uint32_t gi = pass * 16 + kc, slot = gi & 3;
          mbar_wait(sb + BAR_GFULL + slot * 8, gi >> 2);
          const uint64_t off = slot * (GSTAGE >> 4);
          wg_fence();
#pragma unroll
          for (int k = 0; k < 4; k++) mma_ss(acc, a0 + off + k * 2, b0 + off + k * 64, 1);
          wg_commit();
          wg_wait<0>();
          if (lane0) mbar_arrive(sb + BAR_GEMPTY + slot * 8);
        }
        pin(acc);
        float ak[16], av[16];
#pragma unroll
        for (int i = 0; i < 16; i++) { ak[i] = acc[i]; av[i] = acc[16 + i]; }
        const int blk = (cta - NMAIN) * 8 + pass * 4 + wg;
        uint32_t n[8];
        float inv;
        stage_kv<false, 1>(av, n, inv, 0, wg, warp, lane, reinterpret_cast<char*>(gs->V + (32 * SEQ + (blk >> 1) * 128) * 32));
        publish_kv<false, 1>(n, inv, sb + OFF_NRM + 4, lane, nullptr);
        stage_kv<true, 1>(ak, n, inv, 0, wg, warp, lane, reinterpret_cast<char*>(gs->K + (32 * SEQ + (blk >> 1) * 128) * 32), blk < 2);
        publish_kv<true, 1>(n, inv, sb + OFF_NRM, lane, gs->kscale + 32 * 128 + blk * 4 + warp);
        __syncwarp();
      }
      if (lane0) mbar_arrive(sb + BAR_ST + wg * 8);
    } else {
      uint32_t n[8];
      {
        Gemm g{sb, sb & 0x3ffff, wg, gempty_addr(sb, tid), 0, lane < 2};
        float acc[64], inv;
        g.first<SEQ_P1>(acc, [] {});
        g.rest<SEQ_P1, 16, 0>(acc);
        if (ct1 < 8) stage_kv<true, 4>(acc, n, inv, sb + OFF_KV + (wg >> 1) * 32768, wg, warp, lane);
        else stage_kv<false, 4>(acc, n, inv, sb + OFF_KV + (wg >> 1) * 32768, wg, warp, lane);
        g.first<SEQ_P2>(acc, [&] {
          fence_async();
          if (ct1 < 8) publish_kv<true, 4>(n, inv, sb + OFF_NRM, lane, gs->kscale + ct1 * 512 + rb1 * 16 + wg * 4 + warp);
          else publish_kv<false, 4>(n, inv, sb + OFF_NRM, lane, nullptr);
          __syncwarp();
          if (lane0) mbar_arrive(sb + BAR_ST + wg * 8);
        });
        g.rest<SEQ_P2, 14, 0>(acc);
        stage_tile<true, 4>(acc, n, inv, sb + warp * 2048, sb + warp * 2048 + 1024, [&](int h) { return q_off(wg, h); }, lane);
        fence_async();
        if (inv != 1.f) n[0] = 0x7c007c00u;
        if (lane < 4) asm volatile("st.shared.f32 [%0], %1;" ::"r"(sb + OFF_QINV + (tid >> 5) * 16 + ((lane & 1) * 2 + (lane >> 1)) * 4), "f"(inv) : "memory");
        __syncwarp();
      }
      __nv_bfloat16* otile = gs->O + (br * SEQ + rb * 256) * 1024 + hg * 128;
      uint32_t sd = (sb & 0x3ffff) >> 4;
      if (wg == 3) asm volatile("bar.arrive 9, 256;" ::: "memory");
      const bool done = attention<false>(sb, wg, kvdesc + sd, k0desc + sd, qdesc + sd, sb, otile, n, nullptr, 0);
      uint32_t sb2, wg2;
      asm volatile("ld.volatile.shared.v2.u32 {%0, %1}, [%2];" : "=r"(sb2), "=r"(wg2) : "r"(sb + OFF_SB + wg * 8) : "memory");
      sb2 = __shfl_sync(~0u, sb2, 0);
      wg2 = __shfl_sync(~0u, wg2, 0);
      const uint32_t t = fresh_tid();
      sd = (sb2 & 0x3ffff) >> 4;
      if (__any_sync(~0u, !done)) attention<true>(sb, wg2, kvdesc + sd, k0desc + sd, qdesc + sd, sb2, otile, n, gs->kscale + (br ? hg * 4 : 32) * 128, br);
      {
        const uint32_t stage = sb2 + (t >> 5) * 2048;
        Gemm g{sb, sb2 & 0x3ffff, wg2, gempty_addr(sb2, t), PH_P4, (t & 30) == 0};
        float acc[64];
        g.release(3);
        g.first<SEQ_P4>(acc, [] {});
        g.rest<SEQ_P4, 12, 3>(acc);
#pragma unroll
        for (int hf = 0; hf < 2; hf++) {
#pragma unroll
          for (int j = 8 * hf; j < 8 * hf + 8; j += 2) {
            stsm4(stage + hf * GSTAGE + (t & 15) * 128 + ((((j & 7) + ((t >> 4) & 1)) ^ (t & 7)) << 4),
                  pack(acc[4 * j], acc[4 * j + 1]), pack(acc[4 * j + 2], acc[4 * j + 3]),
                  pack(acc[4 * j + 4], acc[4 * j + 5]), pack(acc[4 * j + 6], acc[4 * j + 7]));
          }
          fence_async();
          __syncwarp();
          if (elect_one()) tma_store(&maps.out, stage + hf * GSTAGE, br * 1024 + hg * 128 + hf * 64, rb * 256 + (t >> 5) * 16);
        }
        if (elect_one()) asm volatile("cp.async.bulk.commit_group;\ncp.async.bulk.wait_group.read 0;" ::: "memory");
      }
    }
  }
}

typedef CUresult (*EncodeFn)(CUtensorMap*, CUtensorMapDataType, cuuint32_t, void*, const cuuint64_t*, const cuuint64_t*,
                             const cuuint32_t*, const cuuint32_t*, CUtensorMapInterleave, CUtensorMapSwizzle,
                             CUtensorMapL2promotion, CUtensorMapFloatOOBfill);

void make_map(EncodeFn enc, CUtensorMap* m, void* p, uint64_t cols, uint64_t rows, uint32_t bc, uint32_t brows, CUtensorMapSwizzle sw) {
  cuuint64_t dims[2] = {cols, rows}, strides[1] = {cols * 2};
  cuuint32_t box[2] = {bc, brows}, es[2] = {1, 1};
  enc(m, CU_TENSOR_MAP_DATA_TYPE_BFLOAT16, 2, p, dims, strides, box, es, CU_TENSOR_MAP_INTERLEAVE_NONE, sw,
      CU_TENSOR_MAP_L2_PROMOTION_L2_128B, CU_TENSOR_MAP_FLOAT_OOB_FILL_NONE);
}

}

extern "C" void kernel_launch(void* const* d_in, const int* in_sizes, int n_in, void* d_out, int out_size) {
  static EncodeFn enc = nullptr;
  static void* o_ptr = nullptr;
  if (!enc) {
    void* fn = nullptr;
    cudaDriverEntryPointQueryResult qr;
    cudaGetDriverEntryPoint("cuTensorMapEncodeTiled", &fn, cudaEnableDefault, &qr);
    enc = (EncodeFn)fn;
    cudaGetSymbolAddress(&o_ptr, g_scratch);
    cudaFuncSetAttribute(fused_kernel, cudaFuncAttributeMaxDynamicSharedMemorySize, SMEM_BYTES);
  }
  Maps m;
  const CUtensorMapSwizzle S128 = CU_TENSOR_MAP_SWIZZLE_128B, S64 = CU_TENSOR_MAP_SWIZZLE_64B;
  make_map(enc, &m.xA, d_in[0], 1024, SEQ, 64, 128, S128);
  make_map(enc, &m.wq, d_in[1], 1024, 1024, 64, 64, S128);
  make_map(enc, &m.wk, d_in[2], 32, 1024, 32, 64, S64);
  make_map(enc, &m.wv, d_in[3], 32, 1024, 32, 64, S64);
  make_map(enc, &m.woA, d_in[4], 1024, 1024, 64, 64, S128);
  make_map(enc, &m.xB, d_in[5], 1024, SEQ, 64, 128, S128);
  make_map(enc, &m.wqkv, d_in[6], 3072, 1024, 64, 64, S128);
  make_map(enc, &m.woB, d_in[7], 1024, 1024, 64, 64, S128);
  make_map(enc, &m.o, o_ptr, 1024, 2 * SEQ, 64, 128, S128);
  make_map(enc, &m.out, d_out, 2048, SEQ, 64, 16, S128);
  const uint64_t kvdesc = ((uint64_t)((OFF_ONES - OFF_KV) >> 4) << 16) | (32ull << 32) | (2ull << 62);
  fused_kernel<<<NCTA, NTHREADS, SMEM_BYTES>>>((Scratch*)o_ptr, kvdesc + (OFF_KV >> 4), kvdesc + (OFF_KV >> 4) + 3584, (1ull << 16) | (64ull << 32) | (2ull << 62), m);
}
```
